```python
import torch

def _softmax(x, axis=-1):
    return torch.softmax(x, dim=axis)
def _gelu(x):
    return torch.nn.functional.gelu(x, approximate="tanh")
def _silu(x):
    return torch.nn.functional.silu(x)
def _sigmoid(x):
    return torch.sigmoid(x)
def _layernorm(x, axis=-1, eps=1e-5):
    m = x.mean(dim=axis, keepdim=True)
    v = x.var(dim=axis, keepdim=True, unbiased=False)
    return (x - m) / torch.sqrt(v + eps)
def _scatter_add(tgt, idx, src, axis=0):
    return tgt.clone().index_add_(axis, idx, src)
def _segment_sum(src, seg, n):
    out = torch.zeros((n,) + src.shape[1:], dtype=src.dtype)
    return out.index_add_(0, seg, src)
def _pad(x, pw):
    flat = tuple(v for pair in reversed(pw) for v in pair)
    return torch.nn.functional.pad(x, flat)

kernel_name = 'standalone__kv_cache_quant_int4_int2_kv_with_per_channel_or_per_token_scales__decode'

def setup_inputs():

    _w = (lambda a: (lambda t: t.to(torch.bfloat16) if t.is_floating_point() else t)(torch.as_tensor(a)))
    B = 2
    Sq = 1
    Skv = 32768
    Hq = 32
    Hkv = 8
    Dh = 128
    bits = 3
    G = 32
    if G <= 0 or G >= Skv:
        G = max(1, Skv // 2)
    Skv = (Skv // G) * G
    ngk = Skv // G
    qmax = (1 << bits) - 1
    return {
        "q": _w((lambda *s: torch.randn(*s, dtype=torch.bfloat16) * 1.6)(B, Hq, Sq, Dh)),
        "qk": _w(torch.randint(0, qmax + 1, (B, Hkv, Skv, Dh)).to(torch.int32)),
        "qv": _w(torch.randint(0, qmax + 1, (B, Hkv, Skv, Dh)).to(torch.int32)),
        "k_scales": _w(torch.abs((lambda *s: torch.randn(*s, dtype=torch.bfloat16) * 1.6)(B, Hkv, ngk, Dh)) * 0.05 + 0.02),
        "k_zeros": _w((lambda *s: torch.randn(*s, dtype=torch.bfloat16) * 1.6)(B, Hkv, ngk, Dh) + float(qmax) / 2.0),
        "v_scales": _w(torch.abs((lambda *s: torch.randn(*s, dtype=torch.bfloat16) * 0.05)(B, Hkv, Skv, 1)) * 0.05 + 0.02),
        "v_zeros": _w((lambda *s: torch.randn(*s, dtype=torch.bfloat16) * 0.05)(B, Hkv, Skv, 1) + float(qmax) / 2.0),
    }

def reference(q, qk, qv, k_scales, k_zeros, v_scales, v_zeros):
    B, Hq, Sq, Dh = q.shape
    Hkv, Skv = qk.shape[1], qk.shape[2]
    ngk = k_scales.shape[2]
    G = Skv // ngk
    ks = (lambda x, n, axis: torch.repeat_interleave(x, n, dim=axis))(k_scales, G, axis=2)
    kz = (lambda x, n, axis: torch.repeat_interleave(x, n, dim=axis))(k_zeros, G, axis=2)
    k = ((lambda x, dt: x.to(dt))(qk, q.dtype) - kz) * ks
    v = ((lambda x, dt: x.to(dt))(qv, q.dtype) - v_zeros) * v_scales
    rep = Hq // Hkv
    if rep > 1:
        k = (lambda x, n, axis: torch.repeat_interleave(x, n, dim=axis))(k, rep, axis=1)
        v = (lambda x, n, axis: torch.repeat_interleave(x, n, dim=axis))(v, rep, axis=1)
    scale = float(Dh) ** -0.5
    logits = torch.einsum("bhqd,bhkd->bhqk", q, k) * scale
    p = _softmax(logits, axis=-1)
    o = torch.einsum("bhqk,bhkd->bhqd", p, v)
    return o
```

```cpp
#include <cuda_runtime.h>
#include <cuda_bf16.h>
#include <cuda.h>
#include <stdint.h>
#include <float.h>

namespace {

constexpr int kB = 2, kHq = 32, kHkv = 8, kS = 32768, kD = 128, kG = 32;
constexpr int kRep = kHq / kHkv;
constexpr int kBH = kB * kHkv;
constexpr int kSplit = 8;
constexpr int kTok = 64;
constexpr int kUnitsPerBH = kS / kTok;
constexpr int kUnits = kUnitsPerBH / kSplit;
constexpr int kStages = 3;
constexpr int kTile = kTok * kD * 4;
constexpr int kKsBytes = (kTok / kG) * kD * 2;
constexpr int kVsBytes = kTok * 2;
constexpr int kConsumerWarps = 4;
constexpr int kThreads = (kConsumerWarps + 1) * 32;

constexpr int kOffK = 0;
constexpr int kOffV = kOffK + kStages * kTile;
constexpr int kOffKs = kOffV + kStages * kTile;
constexpr int kOffVs = kOffKs + kStages * 2 * kKsBytes;
constexpr int kOffPart = kOffVs + kStages * 2 * kVsBytes;
constexpr int kOffMl = kOffPart + kConsumerWarps * kRep * kD * 4;
constexpr int kOffBar = kOffMl + kConsumerWarps * kRep * 8;
constexpr int kOffFlag = kOffBar + 4 * kStages * 8;
constexpr int kSmemBytes = kOffFlag + 16 + 1024;

__device__ float g_part_o[kBH * kSplit * kRep * kD];
__device__ float2 g_part_ml[kBH * kSplit * kRep];
__device__ unsigned int g_count[kBH * 32];

__device__ __forceinline__ uint32_t smem_u32(const void* p) { return (uint32_t)__cvta_generic_to_shared(p); }
__device__ __forceinline__ void mbar_init(uint32_t bar, uint32_t cnt) {
    asm volatile("mbarrier.init.shared::cta.b64 [%0], %1;" ::"r"(bar), "r"(cnt) : "memory");
}
__device__ __forceinline__ void mbar_expect_tx(uint32_t bar, uint32_t bytes) {
    asm volatile("mbarrier.arrive.expect_tx.shared::cta.b64 _, [%0], %1;" ::"r"(bar), "r"(bytes) : "memory");
}
__device__ __forceinline__ void mbar_arrive(uint32_t bar) {
    asm volatile("mbarrier.arrive.shared::cta.b64 _, [%0];" ::"r"(bar) : "memory");
}
__device__ __forceinline__ void mbar_wait(uint32_t bar, uint32_t parity) {
    uint32_t done;
    int it = 0;
    do {
        asm volatile(
            "{\n.reg .pred p;\nmbarrier.try_wait.parity.shared::cta.b64 p, [%1], %2;\nselp.u32 %0, 1, 0, p;\n}"
            : "=r"(done)
            : "r"(bar), "r"(parity)
            : "memory");
        if (++it > (1 << 24)) __trap();
    } while (!done);
}
__device__ __forceinline__ void bulk_load(uint32_t dst, const void* src, uint32_t bytes, uint32_t bar, uint64_t pol) {
    asm volatile(
        "cp.async.bulk.shared::cluster.global.mbarrier::complete_tx::bytes.L2::cache_hint [%0], [%1], %2, [%3], %4;" ::"r"(dst),
        "l"(src), "r"(bytes), "r"(bar), "l"(pol)
        : "memory");
}
__device__ __forceinline__ void tensor_load_4d(uint32_t dst, const CUtensorMap* m, int c3, uint32_t bar, uint64_t pol) {
    asm volatile(
        "cp.async.bulk.tensor.4d.shared::cluster.global.mbarrier::complete_tx::bytes.L2::cache_hint "
        "[%0], [%1, {%3, %3, %3, %4}], [%2], %5;" ::"r"(dst),
        "l"(m), "r"(bar), "r"(0), "r"(c3), "l"(pol)
        : "memory");
}
__device__ __forceinline__ int4 lds128(uint32_t a) {
    int4 v;
    asm volatile("ld.shared.v4.s32 {%0,%1,%2,%3}, [%4];" : "=r"(v.x), "=r"(v.y), "=r"(v.z), "=r"(v.w) : "r"(a));
    return v;
}
__device__ __forceinline__ uint2 lds64(uint32_t a) {
    uint2 v;
    asm volatile("ld.shared.v2.u32 {%0,%1}, [%2];" : "=r"(v.x), "=r"(v.y) : "r"(a));
    return v;
}
__device__ __forceinline__ uint32_t lds32(uint32_t a) {
    uint32_t v;
    asm volatile("ld.shared.u32 %0, [%1];" : "=r"(v) : "r"(a));
    return v;
}
__device__ __forceinline__ uint32_t pack_bf16(float lo, float hi) {
    uint32_t r;
    asm("cvt.rn.bf16x2.f32 %0, %1, %2;" : "=r"(r) : "f"(hi), "f"(lo));
    return r;
}
__device__ __forceinline__ uint32_t dequant2(int lo, int hi, uint32_t z, uint32_t s) {
    uint32_t x = pack_bf16(__int2float_rn(lo), __int2float_rn(hi));
    uint32_t r;
    asm("sub.rn.bf16x2 %0, %1, %2;" : "=r"(r) : "r"(x), "r"(z));
    asm("mul.rn.bf16x2 %0, %1, %2;" : "=r"(r) : "r"(r), "r"(s));
    return r;
}
__device__ __forceinline__ void mma_bf16(float (&c)[4], uint32_t a0, uint32_t a1, uint32_t a2, uint32_t a3, uint32_t b0,
                                         uint32_t b1) {
    asm volatile(
        "mma.sync.aligned.m16n8k16.row.col.f32.bf16.bf16.f32 {%0,%1,%2,%3}, {%4,%5,%6,%7}, {%8,%9}, {%0,%1,%2,%3};"
        : "+f"(c[0]), "+f"(c[1]), "+f"(c[2]), "+f"(c[3])
        : "r"(a0), "r"(a1), "r"(a2), "r"(a3), "r"(b0), "r"(b1));
}
__device__ __forceinline__ float ex2(float x) {
    float y;
    asm("ex2.approx.ftz.f32 %0, %1;" : "=f"(y) : "f"(x));
    return y;
}

__global__ void __launch_bounds__(kThreads, 1)
kivi_decode_kernel(const __grid_constant__ CUtensorMap map_v, const __nv_bfloat16* __restrict__ q,
                   const int* __restrict__ qk, const __nv_bfloat16* __restrict__ k_scales,
                   const __nv_bfloat16* __restrict__ k_zeros, const __nv_bfloat16* __restrict__ v_scales,
                   const __nv_bfloat16* __restrict__ v_zeros, __nv_bfloat16* __restrict__ out) {
    extern __shared__ uint8_t smem_raw[];
    const uint32_t sb = (smem_u32(smem_raw) + 1023u) & ~1023u;
    uint8_t* smem = smem_raw + (sb - smem_u32(smem_raw));
    const uint32_t bar_kfull = sb + kOffBar;
    const uint32_t bar_vfull = bar_kfull + kStages * 8;
    const uint32_t bar_kempty = bar_vfull + kStages * 8;
    const uint32_t bar_vempty = bar_kempty + kStages * 8;

    const int warp = threadIdx.x >> 5, lane = threadIdx.x & 31;
    const int bh = blockIdx.x / kSplit, r = blockIdx.x % kSplit;
    const int unit0 = bh * kUnitsPerBH + r;

    if (warp == kConsumerWarps) {
        if (lane == 0) {
            asm volatile("prefetch.tensormap [%0];" ::"l"(&map_v) : "memory");
#pragma unroll
            for (int s = 0; s < kStages; s++) {
                mbar_init(bar_kfull + s * 8, 1);
                mbar_init(bar_vfull + s * 8, 1);
                mbar_init(bar_kempty + s * 8, kConsumerWarps);
                mbar_init(bar_vempty + s * 8, kConsumerWarps);
            }
            asm volatile("fence.mbarrier_init.release.cluster;" ::: "memory");
        }
        uint64_t pol;
        asm volatile("createpolicy.fractional.L2::evict_first.b64 %0, 1.0;" : "=l"(pol));
        const char* gk = reinterpret_cast<const char*>(qk);
        const char* gks = reinterpret_cast<const char*>(k_scales);
        const char* gkz = reinterpret_cast<const char*>(k_zeros);
        const char* gvs = reinterpret_cast<const char*>(v_scales);
        const char* gvz = reinterpret_cast<const char*>(v_zeros);
        auto issue_k = [&](int i, int s) {
            const int u = unit0 + i * kSplit;
            const uint32_t bar = bar_kfull + s * 8;
            mbar_expect_tx(bar, kTile + 2 * kKsBytes);
            bulk_load(sb + kOffK + s * kTile, gk + (size_t)u * kTile, kTile, bar, pol);
            bulk_load(sb + kOffKs + s * 2 * kKsBytes, gks + (size_t)u * kKsBytes, kKsBytes, bar, pol);
            bulk_load(sb + kOffKs + s * 2 * kKsBytes + kKsBytes, gkz + (size_t)u * kKsBytes, kKsBytes, bar, pol);
        };
        auto issue_v = [&](int i, int s) {
            const int u = unit0 + i * kSplit;
            const uint32_t bar = bar_vfull + s * 8;
            mbar_expect_tx(bar, kTile + 2 * kVsBytes);
            tensor_load_4d(sb + kOffV + s * kTile, &map_v, u * (kTok / 8), bar, pol);
            bulk_load(sb + kOffVs + s * 2 * kVsBytes, gvs + (size_t)u * kVsBytes, kVsBytes, bar, pol);
            bulk_load(sb + kOffVs + s * 2 * kVsBytes + kVsBytes, gvz + (size_t)u * kVsBytes, kVsBytes, bar, pol);
        };
        if (lane == 0) {
#pragma unroll
            for (int s = 0; s < kStages; s++) {
                issue_k(s, s);
                issue_v(s, s);
            }
        }
        __syncthreads();
        if (lane == 0) {
            int s = 0;
            uint32_t ph = 0;
            for (int i = kStages; i < kUnits; i++) {
                mbar_wait(bar_kempty + s * 8, ph);
                issue_k(i, s);
                mbar_wait(bar_vempty + s * 8, ph);
                issue_v(i, s);
                if (++s == kStages) {
                    s = 0;
                    ph ^= 1;
                }
            }
        }
        return;
    }

    const int g = lane >> 2, c = lane & 3;
    const int par = g & 1;
    uint2 qf[4][2];
    {
        const __nv_bfloat16* qrow = q + (size_t)(bh * kRep + (g & 3)) * kD + 4 * c;
#pragma unroll
        for (int P = 0; P < 4; P++) {
            qf[P][0] = __ldg(reinterpret_cast<const uint2*>(qrow + 32 * P));
            qf[P][1] = __ldg(reinterpret_cast<const uint2*>(qrow + 32 * P + 16));
        }
    }
    __syncthreads();

    const uint32_t k_lane = (16 * warp + g) * 512 + c * 16;
    const uint32_t k_h0 = par * 64, k_h1 = (par ^ 1) * 64;
    const uint32_t ks_lane = (warp >> 1) * (kD * 2) + c * 8;
    const uint32_t ks_h0 = par * 32, ks_h1 = (par ^ 1) * 32;
    const uint32_t v_lane0 = 2 * warp * 4096 + (2 * c) * 128 + ((g ^ (2 * c)) * 16);
    const uint32_t v_lane1 = 2 * warp * 4096 + (2 * c + 1) * 128 + ((g ^ (2 * c + 1)) * 16);
    const uint32_t vs_lane = (16 * warp + 2 * c) * 2;

    const float sl2e = 0.08838834764831845f * 1.4426950408889634f;
    float acc[4][2][4];
#pragma unroll
    for (int j = 0; j < 4; j++)
#pragma unroll
        for (int m = 0; m < 2; m++)
#pragma unroll
            for (int e = 0; e < 4; e++) acc[j][m][e] = 0.f;
    float m_run = -FLT_MAX, l_run = 0.f;

    int s = 0;
    uint32_t ph = 0;
    for (int i = 0; i < kUnits; i++) {
        mbar_wait(bar_kfull + s * 8, ph);
        const uint32_t kb = sb + kOffK + s * kTile + k_lane;
        const uint32_t ksb = sb + kOffKs + s * 2 * kKsBytes + ks_lane;
        float s0[4] = {0.f, 0.f, 0.f, 0.f}, s1[4] = {0.f, 0.f, 0.f, 0.f};
#pragma unroll
        for (int P = 0; P < 4; P++) {
#pragma unroll
            for (int e = 0; e < 2; e++) {
                const uint32_t ko = P * 128 + (e ? k_h1 : k_h0);
                const uint32_t so = P * 64 + (e ? ks_h1 : ks_h0);
                const int4 x0 = lds128(kb + ko);
                const int4 x1 = lds128(kb + ko + 8 * 512);
                const uint2 sc = lds64(ksb + so);
                const uint2 zr = lds64(ksb + so + kKsBytes);
                mma_bf16(s0, qf[P][e].x, qf[P][e ^ 1].x, qf[P][e].y, qf[P][e ^ 1].y, dequant2(x0.x, x0.y, zr.x, sc.x),
                         dequant2(x0.z, x0.w, zr.y, sc.y));
                mma_bf16(s1, qf[P][e].x, qf[P][e ^ 1].x, qf[P][e].y, qf[P][e ^ 1].y, dequant2(x1.x, x1.y, zr.x, sc.x),
                         dequant2(x1.z, x1.w, zr.y, sc.y));
            }
        }
        __syncwarp();
        if (lane == 0) mbar_arrive(bar_kempty + s * 8);

        const float t0 = s0[0] * sl2e, t1 = s0[3] * sl2e, t2 = s1[0] * sl2e, t3 = s1[3] * sl2e;
        float mx = fmaxf(fmaxf(t0, t1), fmaxf(t2, t3));
        mx = fmaxf(mx, __shfl_xor_sync(0xffffffffu, mx, 1));
        mx = fmaxf(mx, __shfl_xor_sync(0xffffffffu, mx, 2));
        if (__any_sync(0xffffffffu, mx > m_run)) {
            const float m_new = fmaxf(m_run, mx);
            const float alpha = ex2(m_run - m_new);
            m_run = m_new;
            l_run *= alpha;
            const float a0 = __shfl_sync(0xffffffffu, alpha, ((2 * c) & 3) * 4);
            const float a1 = __shfl_sync(0xffffffffu, alpha, ((2 * c + 1) & 3) * 4);
#pragma unroll
            for (int j = 0; j < 4; j++)
#pragma unroll
                for (int m = 0; m < 2; m++) {
                    acc[j][m][0] *= a0;
                    acc[j][m][1] *= a1;
                    acc[j][m][2] *= a0;
                    acc[j][m][3] *= a1;
                }
        }
        const float p0 = ex2(t0 - m_run), p1 = ex2(t1 - m_run), p2 = ex2(t2 - m_run), p3 = ex2(t3 - m_run);
        l_run += (p0 + p1) + (p2 + p3);
        uint32_t b0 = pack_bf16(p0, p1), b1 = pack_bf16(p2, p3);
        if (g >= 4) {
            b0 = pack_bf16(p0 - __uint_as_float(b0 << 16), p1 - __uint_as_float(b0 & 0xffff0000u));
            b1 = pack_bf16(p2 - __uint_as_float(b1 << 16), p3 - __uint_as_float(b1 & 0xffff0000u));
        }

        mbar_wait(bar_vfull + s * 8, ph);
        const uint32_t vb = sb + kOffV + s * kTile;
        const uint32_t vsb = sb + kOffVs + s * 2 * kVsBytes + vs_lane;
        const uint32_t vs_lo = lds32(vsb), vs_hi = lds32(vsb + 16);
        const uint32_t vz_lo = lds32(vsb + kVsBytes), vz_hi = lds32(vsb + kVsBytes + 16);
#pragma unroll
        for (int j = 0; j < 4; j++) {
            const int4 x0 = lds128(vb + v_lane0 + j * 1024);
            const int4 x1 = lds128(vb + v_lane1 + j * 1024);
            const int4 x2 = lds128(vb + v_lane0 + j * 1024 + 4096);
            const int4 x3 = lds128(vb + v_lane1 + j * 1024 + 4096);
            mma_bf16(acc[j][0], dequant2(x0.x, x1.x, vz_lo, vs_lo), dequant2(x0.y, x1.y, vz_lo, vs_lo),
                     dequant2(x2.x, x3.x, vz_hi, vs_hi), dequant2(x2.y, x3.y, vz_hi, vs_hi), b0, b1);
            mma_bf16(acc[j][1], dequant2(x0.z, x1.z, vz_lo, vs_lo), dequant2(x0.w, x1.w, vz_lo, vs_lo),
                     dequant2(x2.z, x3.z, vz_hi, vs_hi), dequant2(x2.w, x3.w, vz_hi, vs_hi), b0, b1);
        }
        __syncwarp();
        if (lane == 0) mbar_arrive(bar_vempty + s * 8);
        if (++s == kStages) {
            s = 0;
            ph ^= 1;
        }
    }

    float* part = reinterpret_cast<float*>(smem + kOffPart);
    float2* ml = reinterpret_cast<float2*>(smem + kOffMl);
    l_run += __shfl_xor_sync(0xffffffffu, l_run, 1);
    l_run += __shfl_xor_sync(0xffffffffu, l_run, 2);
    if (c == 0 && g < 4) ml[warp * kRep + g] = make_float2(m_run, l_run);
    {
        const int hsel = c >> 1;
        const int head = 2 * (c & 1) + hsel;
#pragma unroll
        for (int j = 0; j < 4; j++) {
            float o[4];
#pragma unroll
            for (int m = 0; m < 2; m++)
#pragma unroll
                for (int e = 0; e < 2; e++) {
                    const float keep = hsel ? acc[j][m][2 * e + 1] : acc[j][m][2 * e];
                    const float send = hsel ? acc[j][m][2 * e] : acc[j][m][2 * e + 1];
                    o[2 * m + e] = keep + __shfl_xor_sync(0xffffffffu, send, 2);
                }
            *reinterpret_cast<float4*>(part + (warp * kRep + head) * kD + 32 * j + 4 * g) = make_float4(o[0], o[1], o[2], o[3]);
        }
    }
    asm volatile("bar.sync 1, 128;" ::: "memory");
    const int head = warp, d0 = lane * 4;
    {
        float2 w[kConsumerWarps];
        float M = -FLT_MAX;
#pragma unroll
        for (int k = 0; k < kConsumerWarps; k++) {
            w[k] = ml[k * kRep + head];
            M = fmaxf(M, w[k].x);
        }
        float L = 0.f;
        float4 o = make_float4(0.f, 0.f, 0.f, 0.f);
#pragma unroll
        for (int k = 0; k < kConsumerWarps; k++) {
            const float a = ex2(w[k].x - M);
            const float4 v = *reinterpret_cast<const float4*>(part + (k * kRep + head) * kD + d0);
            L += a * w[k].y;
            o.x += a * v.x;
            o.y += a * v.y;
            o.z += a * v.z;
            o.w += a * v.w;
        }
        __stcg(reinterpret_cast<float4*>(g_part_o + (blockIdx.x * kRep + head) * kD + d0), o);
        if (lane == 0) __stcg(g_part_ml + blockIdx.x * kRep + head, make_float2(M, L));
    }
    __threadfence();
    asm volatile("bar.sync 1, 128;" ::: "memory");
    volatile unsigned int* flag = reinterpret_cast<volatile unsigned int*>(smem + kOffFlag);
    if (threadIdx.x == 0) *flag = atomicAdd(&g_count[bh * 32], 1u);
    asm volatile("bar.sync 1, 128;" ::: "memory");
    if (*flag == kSplit - 1) {
        __threadfence();
        float2 w[kSplit];
        float4 v[kSplit];
#pragma unroll
        for (int k = 0; k < kSplit; k++) {
            w[k] = __ldcg(g_part_ml + (bh * kSplit + k) * kRep + head);
            v[k] = __ldcg(reinterpret_cast<const float4*>(g_part_o + ((bh * kSplit + k) * kRep + head) * kD + d0));
        }
        float M = -FLT_MAX;
#pragma unroll
        for (int k = 0; k < kSplit; k++) M = fmaxf(M, w[k].x);
        float L = 0.f;
        float4 o = make_float4(0.f, 0.f, 0.f, 0.f);
#pragma unroll
        for (int k = 0; k < kSplit; k++) {
            const float a = ex2(w[k].x - M);
            L += a * w[k].y;
            o.x += a * v[k].x;
            o.y += a * v[k].y;
            o.z += a * v[k].z;
            o.w += a * v[k].w;
        }
        const float inv = 1.f / L;
        uint2 res;
        res.x = pack_bf16(o.x * inv, o.y * inv);
        res.y = pack_bf16(o.z * inv, o.w * inv);
        *reinterpret_cast<uint2*>(out + (size_t)(bh * kRep + head) * kD + d0) = res;
        if (threadIdx.x == 0) g_count[bh * 32] = 0;
    }
}

typedef CUresult (*EncodeTiledFn)(CUtensorMap*, CUtensorMapDataType, cuuint32_t, void*, const cuuint64_t*,
                                  const cuuint64_t*, const cuuint32_t*, const cuuint32_t*, CUtensorMapInterleave,
                                  CUtensorMapSwizzle, CUtensorMapL2promotion, CUtensorMapFloatOOBfill);

}

extern "C" void kernel_launch(void* const* d_in, const int* in_sizes, int n_in, void* d_out, int out_size) {
    (void)in_sizes;
    (void)n_in;
    (void)out_size;
    static EncodeTiledFn encode = nullptr;
    if (!encode) {
        cudaDriverEntryPointQueryResult qr;
        void* fn = nullptr;
        cudaGetDriverEntryPoint("cuTensorMapEncodeTiled", &fn, cudaEnableDefault, &qr);
        encode = (EncodeTiledFn)fn;
        cudaFuncSetAttribute(kivi_decode_kernel, cudaFuncAttributeMaxDynamicSharedMemorySize, kSmemBytes);
    }
    CUtensorMap map_v;
    const cuuint64_t gdim[4] = {32, 8, 4, (cuuint64_t)kBH * kS / 8};
    const cuuint64_t gstr[3] = {512, 128, 4096};
    const cuuint32_t box[4] = {32, 8, 4, kTok / 8};
    const cuuint32_t estr[4] = {1, 1, 1, 1};
    encode(&map_v, CU_TENSOR_MAP_DATA_TYPE_INT32, 4, d_in[2], gdim, gstr, box, estr, CU_TENSOR_MAP_INTERLEAVE_NONE,
           CU_TENSOR_MAP_SWIZZLE_128B, CU_TENSOR_MAP_L2_PROMOTION_NONE, CU_TENSOR_MAP_FLOAT_OOB_FILL_NONE);

    kivi_decode_kernel<<<kBH * kSplit, kThreads, kSmemBytes>>>(
        map_v, (const __nv_bfloat16*)d_in[0], (const int*)d_in[1], (const __nv_bfloat16*)d_in[3],
        (const __nv_bfloat16*)d_in[4], (const __nv_bfloat16*)d_in[5], (const __nv_bfloat16*)d_in[6],
        (__nv_bfloat16*)d_out);
}
```

```cpp
#include <cuda_runtime.h>
#include <cuda_bf16.h>
#include <cuda.h>
#include <stdint.h>
#include <float.h>

#define WARM 0
#define D0 7.0
#define D1 3.0
#define J0 80
#define J1 120
#define STAG 0
#define NC 4
#define POLL_AT 1
#define INIT_AT 56
#define SPIN 0

namespace {

constexpr int kB = 2, kHq = 32, kHkv = 8, kS = 32768, kD = 128, kG = 32;
constexpr int kRep = kHq / kHkv;
constexpr int kBH = kB * kHkv;
constexpr int kSplit = 8;
constexpr int kCtas = kBH * kSplit;
constexpr int kTok = 64;
constexpr int kUnitsPerBH = kS / kTok;
constexpr int kUnits = kUnitsPerBH / kSplit;
constexpr int kStages = 3;
constexpr int kVsRing = 8;
constexpr int kTile = kTok * kD * 4;
constexpr int kKsBytes = (kTok / kG) * kD * 2;
constexpr int kVsBytes = kTok * 2;
constexpr int kCW = NC;
constexpr int kNT = 8 / kCW;
constexpr int kThreads = (5 + kCW) * 32;
constexpr int kRow = kD + 8;
constexpr uint32_t kProgTotal = kCtas * 2 * kUnits;

constexpr int kOffK = 0;
constexpr int kOffV = kOffK + kStages * kTile;
constexpr int kOffKs = kOffV + kStages * kTile;
constexpr int kOffVs = kOffKs + kStages * 2 * kKsBytes;
constexpr int kOffSc = kOffVs + kVsRing * 2 * kVsBytes;
constexpr int kOffPart = kOffSc + 2 * 1024;
constexpr int kOffBar = kOffPart + kRep * kRow * 4;
constexpr int kOffTag = kOffBar + 4 * kStages * 8;
constexpr int kSmemBytes = kOffTag + 16 + 1024;

__device__ __align__(128) uint32_t g_part[kCtas * kRep * kRow];
__device__ unsigned int g_prog[32];

#define TSTAMP(k)
#define TGET(v)
#define TPUT(k,v)

__device__ __forceinline__ uint32_t smem_u32(const void* p) { return (uint32_t)__cvta_generic_to_shared(p); }
__device__ __forceinline__ bool elect_one() {
    uint32_t p;
    asm volatile("{\n.reg .pred P;\nelect.sync _|P, 0xffffffff;\nselp.u32 %0, 1, 0, P;\n}" : "=r"(p));
    return p != 0;
}
__device__ __forceinline__ void mbar_init(uint32_t bar, uint32_t cnt) {
    asm volatile("mbarrier.init.shared::cta.b64 [%0], %1;" ::"r"(bar), "r"(cnt) : "memory");
}
__device__ __forceinline__ void mbar_expect_tx(uint32_t bar, uint32_t bytes) {
    asm volatile("mbarrier.arrive.expect_tx.shared::cta.b64 _, [%0], %1;" ::"r"(bar), "r"(bytes) : "memory");
}
__device__ __forceinline__ void mbar_arrive(uint32_t bar) {
    asm volatile("mbarrier.arrive.shared::cta.b64 _, [%0];" ::"r"(bar) : "memory");
}
__device__ __forceinline__ void mbar_wait(uint32_t bar, uint32_t parity) {
    uint32_t done;
    int it = 0;
    do {
        asm volatile(
            "{\n.reg .pred p;\nmbarrier.try_wait.parity.shared::cta.b64 p, [%1], %2;\nselp.u32 %0, 1, 0, p;\n}"
            : "=r"(done)
            : "r"(bar), "r"(parity)
            : "memory");
        if (++it > (1 << 24)) __trap();
    } while (!done);
}
__device__ __forceinline__ void mbar_spin(uint32_t bar, uint32_t parity) {
    uint32_t done;
    int it = 0;
    do {
        asm volatile(
            "{\n.reg .pred p;\nmbarrier.test_wait.parity.shared::cta.b64 p, [%1], %2;\nselp.u32 %0, 1, 0, p;\n}"
            : "=r"(done)
            : "r"(bar), "r"(parity)
            : "memory");
        if (++it > (1 << 26)) __trap();
    } while (!done);
}
__device__ __forceinline__ void bulk_load(uint32_t dst, const void* src, uint32_t bytes, uint32_t bar, uint64_t pol) {
    asm volatile(
        "cp.async.bulk.shared::cluster.global.mbarrier::complete_tx::bytes.L2::cache_hint [%0], [%1], %2, [%3], %4;" ::"r"(dst),
        "l"(src), "r"(bytes), "r"(bar), "l"(pol)
        : "memory");
}
__device__ __forceinline__ void tensor_load_4d(uint32_t dst, const CUtensorMap* m, int c3, uint32_t bar, uint64_t pol) {
    asm volatile(
        "cp.async.bulk.tensor.4d.shared::cluster.global.mbarrier::complete_tx::bytes.L2::cache_hint "
        "[%0], [%1, {%3, %3, %3, %4}], [%2], %5;" ::"r"(dst),
        "l"(m), "r"(bar), "r"(0), "r"(c3), "l"(pol)
        : "memory");
}
__device__ __forceinline__ int4 lds128(uint32_t a) {
    int4 v;
    asm volatile("ld.shared.v4.s32 {%0,%1,%2,%3}, [%4];" : "=r"(v.x), "=r"(v.y), "=r"(v.z), "=r"(v.w) : "r"(a));
    return v;
}
__device__ __forceinline__ float4 lds128f(uint32_t a) {
    float4 v;
    asm volatile("ld.shared.v4.f32 {%0,%1,%2,%3}, [%4];" : "=f"(v.x), "=f"(v.y), "=f"(v.z), "=f"(v.w) : "r"(a));
    return v;
}
__device__ __forceinline__ void sts128f(uint32_t a, float x, float y, float z, float w) {
    asm volatile("st.shared.v4.f32 [%0], {%1,%2,%3,%4};" ::"r"(a), "f"(x), "f"(y), "f"(z), "f"(w) : "memory");
}
__device__ __forceinline__ void sts64f(uint32_t a, float x, float y) {
    asm volatile("st.shared.v2.f32 [%0], {%1,%2};" ::"r"(a), "f"(x), "f"(y) : "memory");
}
__device__ __forceinline__ uint2 lds64(uint32_t a) {
    uint2 v;
    asm volatile("ld.shared.v2.u32 {%0,%1}, [%2];" : "=r"(v.x), "=r"(v.y) : "r"(a));
    return v;
}
__device__ __forceinline__ uint32_t lds32(uint32_t a) {
    uint32_t v;
    asm volatile("ld.shared.u32 %0, [%1];" : "=r"(v) : "r"(a));
    return v;
}
__device__ __forceinline__ uint32_t ld_relaxed(const unsigned int* p) {
    uint32_t v;
    asm volatile("ld.relaxed.gpu.global.u32 %0, [%1];" : "=r"(v) : "l"(p) : "memory");
    return v;
}
__device__ __forceinline__ uint4 ld_relaxed4(const uint32_t* p) {
    uint4 v;
    asm volatile("ld.relaxed.gpu.global.v4.u32 {%0,%1,%2,%3}, [%4];" : "=r"(v.x), "=r"(v.y), "=r"(v.z), "=r"(v.w) : "l"(p) : "memory");
    return v;
}
__device__ __forceinline__ uint2 ld_relaxed2(const uint32_t* p) {
    uint2 v;
    asm volatile("ld.relaxed.gpu.global.v2.u32 {%0,%1}, [%2];" : "=r"(v.x), "=r"(v.y) : "l"(p) : "memory");
    return v;
}
__device__ __forceinline__ void st_relaxed4(uint32_t* p, uint4 v) {
    asm volatile("st.relaxed.gpu.global.v4.u32 [%0], {%1,%2,%3,%4};" ::"l"(p), "r"(v.x), "r"(v.y), "r"(v.z), "r"(v.w) : "memory");
}
__device__ __forceinline__ void st_relaxed4_if(bool p_, uint32_t* p, uint4 v) {
    asm volatile("{\n.reg .pred P;\nsetp.ne.u32 P, %5, 0;\n@P st.relaxed.gpu.global.v4.u32 [%0], {%1,%2,%3,%4};\n}" ::"l"(p), "r"(v.x), "r"(v.y), "r"(v.z), "r"(v.w), "r"((uint32_t)p_) : "memory");
}
__device__ __forceinline__ void st_relaxed2_if(bool p_, uint32_t* p, uint2 v) {
    asm volatile("{\n.reg .pred P;\nsetp.ne.u32 P, %3, 0;\n@P st.relaxed.gpu.global.v2.u32 [%0], {%1,%2};\n}" ::"l"(p), "r"(v.x), "r"(v.y), "r"((uint32_t)p_) : "memory");
}
__device__ __forceinline__ void st_weak2_if(bool p_, void* p, uint2 v) {
    asm volatile("{\n.reg .pred P;\nsetp.ne.u32 P, %3, 0;\n@P st.global.v2.u32 [%0], {%1,%2};\n}" ::"l"(p), "r"(v.x), "r"(v.y), "r"((uint32_t)p_) : "memory");
}
__device__ __forceinline__ void red_inc_if(bool p_, unsigned int* p) {
    asm volatile("{\n.reg .pred P;\nsetp.ne.u32 P, %1, 0;\n@P red.relaxed.gpu.global.add.u32 [%0], 1;\n}" ::"l"(p), "r"((uint32_t)p_) : "memory");
}
__device__ __forceinline__ uint32_t pack_bf16(float lo, float hi) {
    uint32_t r;
    asm("cvt.rn.bf16x2.f32 %0, %1, %2;" : "=r"(r) : "f"(hi), "f"(lo));
    return r;
}
__device__ __forceinline__ uint32_t dequant2(int lo, int hi, uint32_t z, uint32_t s) {
    uint32_t x = pack_bf16(__int2float_rn(lo), __int2float_rn(hi));
    uint32_t r;
    asm("sub.rn.bf16x2 %0, %1, %2;" : "=r"(r) : "r"(x), "r"(z));
    asm("mul.rn.bf16x2 %0, %1, %2;" : "=r"(r) : "r"(r), "r"(s));
    return r;
}
__device__ __forceinline__ void mma_bf16(float (&c)[4], uint32_t a0, uint32_t a1, uint32_t a2, uint32_t a3, uint32_t b0,
                                         uint32_t b1) {
    asm("mma.sync.aligned.m16n8k16.row.col.f32.bf16.bf16.f32 {%0,%1,%2,%3}, {%4,%5,%6,%7}, {%8,%9}, {%0,%1,%2,%3};"
        : "+f"(c[0]), "+f"(c[1]), "+f"(c[2]), "+f"(c[3])
        : "r"(a0), "r"(a1), "r"(a2), "r"(a3), "r"(b0), "r"(b1));
}
__device__ __forceinline__ float ex2(float x) {
    float y;
    asm("ex2.approx.ftz.f32 %0, %1;" : "=f"(y) : "f"(x));
    return y;
}
__device__ __forceinline__ uint32_t tagged(float x, uint32_t tag) { return (__float_as_uint(x) & ~1u) | tag; }
__device__ __forceinline__ uint32_t split_p(float a, float b, bool lo) {
    uint32_t h = pack_bf16(a, b);
    if (lo) h = pack_bf16(a - __uint_as_float(h << 16), b - __uint_as_float(h & 0xffff0000u));
    return h;
}
__device__ __forceinline__ uint32_t pin(uint32_t x) { return __shfl_sync(0xffffffffu, x, threadIdx.x & 31); }
template <typename T>
__device__ __forceinline__ T* pin(T* p) {
    const uint64_t a = reinterpret_cast<uint64_t>(p);
    return reinterpret_cast<T*>((uint64_t)pin((uint32_t)(a >> 32)) << 32 | pin((uint32_t)a));
}

__global__ void __launch_bounds__(kThreads, 1)
kivi_decode_kernel(const int* __restrict__ qk, const __nv_bfloat16* __restrict__ k_scales,
                   const __nv_bfloat16* __restrict__ k_zeros, const __nv_bfloat16* __restrict__ v_scales,
                   const __nv_bfloat16* __restrict__ v_zeros, const __nv_bfloat16* __restrict__ q,
                   __nv_bfloat16* __restrict__ out, const __grid_constant__ CUtensorMap map_v) {
    extern __shared__ uint8_t smem_raw[];
    unsigned long long t0 = 0, t1 = 0, t2 = 0;
    TGET(t0);
    const uint32_t sb = (smem_u32(smem_raw) + 1023u) & ~1023u;
    const uint32_t bar_kfull = sb + kOffBar;
    const uint32_t bar_kempty = bar_kfull + kStages * 8;
    const uint32_t bar_vempty = bar_kempty + kStages * 8;
    const uint32_t bar_vfull = bar_vempty + kStages * 8;
    constexpr uint32_t kKTx = kTile + 2 * kKsBytes + 2 * kVsBytes;

    const int bh = blockIdx.x / kSplit, r = blockIdx.x % kSplit;
    const int unit0 = bh * kUnitsPerBH + r;
    uint64_t pol;
    asm volatile("createpolicy.fractional.L2::evict_first.b64 %0, 1.0;" : "=l"(pol));
    const char* gk = reinterpret_cast<const char*>(qk);

    if (threadIdx.x < 32) {
        if (elect_one()) {
            mbar_init(bar_kfull, 1);
            asm volatile("fence.mbarrier_init.release.cluster;" ::: "memory");
            mbar_expect_tx(bar_kfull, kKTx);
            bulk_load(sb + kOffK, gk + (size_t)unit0 * kTile, kTile, bar_kfull, pol);
            TGET(t1);
        }
        __syncwarp();
    }

    const int warp = __shfl_sync(0xffffffffu, threadIdx.x >> 5, 0), lane = threadIdx.x & 31;
    const bool merger = (r == kSplit - 1);

    if (warp == 0 || warp > kCW) {
        if (warp == 0) {
            const char* gks = reinterpret_cast<const char*>(k_scales);
            const char* gkz = reinterpret_cast<const char*>(k_zeros);
            const char* gvs = reinterpret_cast<const char*>(v_scales);
            const char* gvz = reinterpret_cast<const char*>(v_zeros);
            auto issue_scales = [&](int i, int s) {
                const int u = unit0 + i * kSplit;
                const uint32_t bar = bar_kfull + s * 8;
                const uint32_t vsd = sb + kOffVs + (i & (kVsRing - 1)) * 2 * kVsBytes;
                bulk_load(sb + kOffKs + s * 2 * kKsBytes, gks + (size_t)u * kKsBytes, kKsBytes, bar, pol);
                bulk_load(sb + kOffKs + s * 2 * kKsBytes + kKsBytes, gkz + (size_t)u * kKsBytes, kKsBytes, bar, pol);
                bulk_load(vsd, gvs + (size_t)u * kVsBytes, kVsBytes, bar, pol);
                bulk_load(vsd + kVsBytes, gvz + (size_t)u * kVsBytes, kVsBytes, bar, pol);
            };
            if (elect_one()) {
                asm volatile("prefetch.tensormap [%0];" ::"l"(&map_v) : "memory");
                issue_scales(0, 0);
#pragma unroll
                for (int s = 0; s < kStages; s++) {
                    if (s) mbar_init(bar_kfull + s * 8, 1);
                    mbar_init(bar_kempty + s * 8, kCW);
                    mbar_init(bar_vempty + s * 8, kCW);
                    mbar_init(bar_vfull + s * 8, 1);
                }
                asm volatile("fence.mbarrier_init.release.cluster;" ::: "memory");
            }
            __syncwarp();
            asm volatile("bar.arrive 0, %0;" ::"n"(32 + kCW * 32) : "memory");
            if (elect_one()) {
                const int stag = STAG == 0   ? 0
                                 : STAG == 1 ? (int)(__brev(blockIdx.x) >> 25) - 64
                                 : STAG == 2 ? (merger ? 32 : 0)
                                 : STAG == 3 ? (merger ? 64 : 0)
                                             : (merger ? 64 + bh : (r * 16 + bh) / 2 - 32);
                uint32_t seen = 0;
                bool pace = true;
                auto throttle = [&](int j) {
                    constexpr int d0 = (int)(D0 * kCtas), d1 = (int)(D1 * kCtas);
                    const int dj = j <= J0 ? d0 : j >= J1 ? d1 : d0 + (d1 - d0) * (j - J0) / (J1 - J0);
                    const int need = (j + 1) * kCtas - dj + stag;
                    int it = 0;
                    while (pace && (int)seen < need) {
                        seen = ld_relaxed(&g_prog[0]) & (kProgTotal - 1);
                        if (++it > 128) pace = false;
                    }
                };
                int s = 0;
                uint32_t ph = 1;
#pragma unroll 1
                for (int i = 0; i < kUnits; i++) {
                    int s1 = s + 1;
                    uint32_t ph1 = ph;
                    if (s1 == kStages) {
                        s1 = 0;
                        ph1 ^= 1;
                    }
                    if (i + 1 < kUnits) {
                        throttle(2 * i + 1);
                        mbar_wait(bar_kempty + s1 * 8, ph1);
                        mbar_expect_tx(bar_kfull + s1 * 8, kKTx);
                        bulk_load(sb + kOffK + s1 * kTile, gk + (size_t)(unit0 + (i + 1) * kSplit) * kTile, kTile, bar_kfull + s1 * 8, pol);
                        issue_scales(i + 1, s1);
                    }
                    throttle(i + 1 < kUnits ? 2 * i + 2 : 2 * i + 1);
                    mbar_wait(bar_vempty + s * 8, ph);
                    mbar_expect_tx(bar_vfull + s * 8, kTile);
                    tensor_load_4d(sb + kOffV + s * kTile, &map_v, (unit0 + i * kSplit) * (kTok / 8), bar_vfull + s * 8, pol);
                    if (i == 1) TGET(t2);
                    if (i == 8) {
                        const uint32_t tag = ((ld_relaxed(&g_prog[0]) / kProgTotal) & 1) ^ 1;
                        asm volatile("st.shared.u32 [%0], %1;" ::"r"(sb + kOffTag), "r"(tag) : "memory");
                    }
                    s = s1;
                    ph = ph1;
                }
                TPUT(0, t0); TPUT(1, t1); TPUT(2, t2);
            }
            return;
        }
        if (!merger) return;
        const int head = warp - kCW - 1;
        const uint32_t* row = pin(g_part + (size_t)(bh * kSplit * kRep + head) * kRow + lane * 4);
        const uint32_t* mlp = g_part + (size_t)((bh * kSplit + (lane & 7)) * kRep + head) * kRow + kD;
        __nv_bfloat16* optr = pin(out + (size_t)(bh * kRep + head) * kD + lane * 4);
        const uint32_t own = pin(sb + kOffPart + (head * kRow + lane * 4) * 4);
        const bool tsl = threadIdx.x == (kCW + 1) * 32;
#pragma unroll 1
        for (int pass = WARM ? 0 : 1; pass < 2; pass++) {
            if (pass) asm volatile("bar.sync 2, 160;" ::: "memory");
            const uint32_t tag = pass ? lds32(sb + kOffTag) : 0;
            uint2 w = lds64(sb + kOffPart + (head * kRow + kD) * 4);
            uint4 v[kSplit - 1];
#pragma unroll
            for (int k = 0; k < kSplit - 1; k++) v[k] = make_uint4(0, 0, 0, 0);
            float wt[kSplit];
            bool have_w = false;
            bool ok = !pass || (lane & 7) == kSplit - 1;
            uint32_t pending = pass ? (1u << (kSplit - 1)) - 1 : 0;
            int it = 0;
            do {
#pragma unroll
                for (int k = 0; k < kSplit - 1; k++)
                    if (pending >> k & 1) v[k] = ld_relaxed4(row + k * (kRep * kRow));
                if (!have_w) {
                    if (!ok) {
                        w = ld_relaxed2(mlp);
                        ok = (((w.x ^ tag) | (w.y ^ tag)) & 1) == 0;
                    }
                    if (__all_sync(0xffffffffu, ok)) {
                        have_w = true;
                        const float mk = __uint_as_float(w.x), lk = __uint_as_float(w.y);
                        float M = fmaxf(mk, __shfl_xor_sync(0xffffffffu, mk, 1));
                        M = fmaxf(M, __shfl_xor_sync(0xffffffffu, M, 2));
                        M = fmaxf(M, __shfl_xor_sync(0xffffffffu, M, 4));
                        float wk = ex2(mk - M);
                        float L = wk * lk;
                        L += __shfl_xor_sync(0xffffffffu, L, 1);
                        L += __shfl_xor_sync(0xffffffffu, L, 2);
                        L += __shfl_xor_sync(0xffffffffu, L, 4);
                        wk = wk / L;
#pragma unroll
                        for (int k = 0; k < kSplit; k++) wt[k] = __shfl_sync(0xffffffffu, wk, k);
                        if (pass && tsl) TSTAMP(13);
                    }
                }
                uint32_t bad = have_w ? 0 : 0x80;
#pragma unroll
                for (int k = 0; k < kSplit - 1; k++)
                    bad |= ((((v[k].x ^ tag) | (v[k].y ^ tag)) | ((v[k].z ^ tag) | (v[k].w ^ tag))) & 1) << k;
                pending = __reduce_or_sync(0xffffffffu, bad);
                if (++it > (1 << 22)) __trap();
            } while (pending);
            if (pass) TGET(t1);
            float4 o = make_float4(0.f, 0.f, 0.f, 0.f);
#pragma unroll
            for (int k = 0; k < kSplit - 1; k++) {
                o.x += wt[k] * __uint_as_float(v[k].x);
                o.y += wt[k] * __uint_as_float(v[k].y);
                o.z += wt[k] * __uint_as_float(v[k].z);
                o.w += wt[k] * __uint_as_float(v[k].w);
            }
            if (pass) asm volatile("bar.sync 3, %0;" ::"n"(kThreads - 32) : "memory");
            const float4 cv = lds128f(own);
            uint2 res;
            res.x = pack_bf16(o.x + wt[kSplit - 1] * cv.x, o.y + wt[kSplit - 1] * cv.y);
            res.y = pack_bf16(o.z + wt[kSplit - 1] * cv.z, o.w + wt[kSplit - 1] * cv.w);
            st_weak2_if(pass, optr, res);
        }
        if (tsl) { TSTAMP(11); TPUT(14, t1); }
        return;
    }

    const int cw = warp - 1;
    const int g = lane >> 2, c = lane & 3;
    const int par = g & 1;
    uint2 qf[4][2];
    {
        const __nv_bfloat16* qrow = q + (size_t)(bh * kRep + (g & 3)) * kD + 4 * c;
#pragma unroll
        for (int P = 0; P < 4; P++) {
            qf[P][0] = __ldg(reinterpret_cast<const uint2*>(qrow + 32 * P));
            qf[P][1] = __ldg(reinterpret_cast<const uint2*>(qrow + 32 * P + 16));
        }
    }
    const uint32_t k_lane0 = sb + kOffK + (8 * kNT * cw + g) * 512 + c * 16 + par * 64;
    const uint32_t ks_lane0 = sb + kOffKs + (cw * kNT / 4) * (kD * 2) + c * 8 + par * 32;
    const int vchunk = kNT == 2 ? g : (cw & 1) * 4 + (g >> 1);
    const uint32_t v_lane0 = pin(sb + kOffV + (cw * kNT / 2) * 1024 + (2 * c) * 128 + ((vchunk ^ (2 * c)) * 16) + (kNT == 2 ? 0 : (g & 1) * 8));
    const uint32_t vs_lane = sb + kOffVs + (2 * c) * 2;
    const uint32_t sc_rd = sb + kOffSc + ((g & 3) * 4 + c) * 16;
    const uint32_t sc_wr = sc_rd + (cw * kNT / 2) * 256 + (kNT == 2 ? 0 : (cw & 1) * 8);
    const int hsel = c >> 1;
    const int ocol = (2 * (c & 1) + hsel) * kRow + 16 * kNT * cw + 2 * kNT * g;
    uint32_t* optr = pin(g_part + (size_t)blockIdx.x * kRep * kRow + ocol);
    const uint32_t osm = pin(sb + kOffPart + ocol * 4);
    const bool reporter = threadIdx.x == 32;

    const float sl2e = 0.08838834764831845f * 1.4426950408889634f;
    float acc[kNT][4];
#pragma unroll
    for (int m = 0; m < kNT; m++)
#pragma unroll
        for (int e = 0; e < 4; e++) acc[m][e] = 0.f;
    float m_run = -FLT_MAX, l_run = 0.f;
    uint32_t tag = 0;

#pragma unroll 1
    for (int pass = WARM ? 0 : 1; pass < 2; pass++) {
        if (pass) {
            asm volatile("bar.sync 0, %0;" ::"n"(32 + kCW * 32) : "memory");
            int sk = 0, sv = 0;
            uint32_t phk = 0, phv = 0;
            uint32_t pb[4][2];
#pragma unroll
            for (int k = 0; k < 4; k++) pb[k][0] = pb[k][1] = 0;
#pragma unroll 1
            for (int i = 0; i <= kUnits; i++) {
                uint32_t pn[4][2];
                float a0 = 1.f, a1 = 1.f;
                if (i < kUnits) {
                    mbar_wait(bar_kfull + sk * 8, phk);
                    if (threadIdx.x == 32 && i == 0) TSTAMP(3);
                    if (threadIdx.x == 32 && i == kUnits - 1) TSTAMP(4);
                    float sa[kNT][2][4];
#pragma unroll
                    for (int u = 0; u < kNT; u++)
#pragma unroll
                        for (int e = 0; e < 2; e++)
#pragma unroll
                            for (int k = 0; k < 4; k++) sa[u][e][k] = 0.f;
#pragma unroll
                    for (int P = 0; P < 4; P++)
#pragma unroll
                        for (int e = 0; e < 2; e++) {
                            const uint32_t ka = (k_lane0 ^ (e * 64)) + sk * kTile + P * 128;
                            const uint32_t sa_ = (ks_lane0 ^ (e * 32)) + sk * (2 * kKsBytes) + P * 64;
                            const uint2 zr = lds64(sa_ + kKsBytes);
                            const uint2 sc = lds64(sa_);
#pragma unroll
                            for (int u = 0; u < kNT; u++) {
                                const int4 x = lds128(ka + u * 8 * 512);
                                mma_bf16(sa[u][e], qf[P][e].x, qf[P][e ^ 1].x, qf[P][e].y, qf[P][e ^ 1].y,
                                         dequant2(x.x, x.y, zr.x, sc.x), dequant2(x.z, x.w, zr.y, sc.y));
                            }
                        }
                    __syncwarp();
                    if (lane == 0) mbar_arrive(bar_kempty + sk * 8);
                    red_inc_if(reporter, &g_prog[0]);
                    if (g < 4) {
                        if (kNT == 2)
                            sts128f(sc_wr + (i & 1) * 1024, (sa[0][0][0] + sa[0][1][0]) * sl2e, (sa[0][0][3] + sa[0][1][3]) * sl2e,
                                    (sa[kNT - 1][0][0] + sa[kNT - 1][1][0]) * sl2e, (sa[kNT - 1][0][3] + sa[kNT - 1][1][3]) * sl2e);
                        else
                            sts64f(sc_wr + (i & 1) * 1024, (sa[0][0][0] + sa[0][1][0]) * sl2e, (sa[0][0][3] + sa[0][1][3]) * sl2e);
                    }
                    if (++sk == kStages) {
                        sk = 0;
                        phk ^= 1;
                    }
                    asm volatile("bar.sync 1, %0;" ::"n"(kCW * 32) : "memory");
                    float4 t[4];
#pragma unroll
                    for (int kk = 0; kk < 4; kk++) t[kk] = lds128f(sc_rd + (i & 1) * 1024 + kk * 256);
                    float mx = m_run;
#pragma unroll
                    for (int kk = 0; kk < 4; kk++) mx = fmaxf(mx, fmaxf(fmaxf(t[kk].x, t[kk].y), fmaxf(t[kk].z, t[kk].w)));
                    mx = fmaxf(mx, __shfl_xor_sync(0xffffffffu, mx, 1));
                    mx = fmaxf(mx, __shfl_xor_sync(0xffffffffu, mx, 2));
                    const float alpha = ex2(m_run - mx);
                    m_run = mx;
                    a0 = __shfl_sync(0xffffffffu, alpha, ((2 * c) & 3) * 4);
                    a1 = __shfl_sync(0xffffffffu, alpha, ((2 * c + 1) & 3) * 4);
                    float ls = 0.f;
#pragma unroll
                    for (int kk = 0; kk < 4; kk++) {
                        const float p0 = ex2(t[kk].x - mx), p1 = ex2(t[kk].y - mx), p2 = ex2(t[kk].z - mx), p3 = ex2(t[kk].w - mx);
                        ls += (p0 + p1) + (p2 + p3);
                        pn[kk][0] = split_p(p0, p1, g >= 4);
                        pn[kk][1] = split_p(p2, p3, g >= 4);
                    }
                    l_run = l_run * alpha + ls;
                    if (i == INIT_AT) {
                        tag = lds32(sb + kOffTag);
                        const uint32_t nt = tag ^ 1;
                        if (kNT == 2) st_relaxed4_if(!merger, optr, make_uint4(nt, nt, nt, nt));
                        else st_relaxed2_if(!merger, optr, make_uint2(nt, nt));
                        st_relaxed4_if(!merger && cw == 0 && g < 4 && c < 2, g_part + (size_t)(blockIdx.x * kRep + (g & 3)) * kRow + kD + (c & 1) * 4, make_uint4(nt, nt, nt, nt));
                    }
                    if (i == kUnits - 1) {
                        if (INIT_AT >= kUnits) tag = lds32(sb + kOffTag);
                        if (cw == 0) {
                            float l = l_run + __shfl_xor_sync(0xffffffffu, l_run, 1);
                            l += __shfl_xor_sync(0xffffffffu, l, 2);
                            if (g < 4 && c < 2) {
                                if (merger)
                                    sts128f(sb + kOffPart + (g * kRow + kD + c * 4) * 4, m_run, l, m_run, l);
                                else
                                    st_relaxed4(g_part + (size_t)(blockIdx.x * kRep + g) * kRow + kD + c * 4,
                                                make_uint4(tagged(m_run, tag), tagged(l, tag), 0, 0));
                            }
                            if (merger) asm volatile("bar.arrive 2, 160;" ::: "memory");
                        }
                    }
                }
                if (i > 0) {
                    const uint32_t va0 = v_lane0 + sv * kTile, va1 = va0 ^ (128 + 16);
                    const uint32_t vsb = vs_lane + ((i - 1) & (kVsRing - 1)) * (2 * kVsBytes);
                    uint32_t vs[4][2], vz[4][2];
#pragma unroll
                    for (int kk = 0; kk < 4; kk++)
#pragma unroll
                        for (int u = 0; u < 2; u++) {
                            vs[kk][u] = lds32(vsb + kk * 32 + u * 16);
                            vz[kk][u] = lds32(vsb + kVsBytes + kk * 32 + u * 16);
                        }
                    if (SPIN) mbar_spin(bar_vfull + sv * 8, phv); else mbar_wait(bar_vfull + sv * 8, phv);
                    if (threadIdx.x == 32 && i == kUnits) TGET(t1);
#pragma unroll
                    for (int kk = 0; kk < 4; kk++) {
                        if (kNT == 2) {
                            const int4 x0 = lds128(va0 + kk * 8192);
                            const int4 x1 = lds128(va1 + kk * 8192);
                            const int4 x2 = lds128(va0 + kk * 8192 + 4096);
                            const int4 x3 = lds128(va1 + kk * 8192 + 4096);
                            mma_bf16(acc[0], dequant2(x0.x, x1.x, vz[kk][0], vs[kk][0]), dequant2(x0.y, x1.y, vz[kk][0], vs[kk][0]),
                                     dequant2(x2.x, x3.x, vz[kk][1], vs[kk][1]), dequant2(x2.y, x3.y, vz[kk][1], vs[kk][1]), pb[kk][0], pb[kk][1]);
                            mma_bf16(acc[kNT - 1], dequant2(x0.z, x1.z, vz[kk][0], vs[kk][0]), dequant2(x0.w, x1.w, vz[kk][0], vs[kk][0]),
                                     dequant2(x2.z, x3.z, vz[kk][1], vs[kk][1]), dequant2(x2.w, x3.w, vz[kk][1], vs[kk][1]), pb[kk][0], pb[kk][1]);
                        } else {
                            const uint2 x0 = lds64(va0 + kk * 8192);
                            const uint2 x1 = lds64(va1 + kk * 8192);
                            const uint2 x2 = lds64(va0 + kk * 8192 + 4096);
                            const uint2 x3 = lds64(va1 + kk * 8192 + 4096);
                            mma_bf16(acc[0], dequant2(x0.x, x1.x, vz[kk][0], vs[kk][0]), dequant2(x0.y, x1.y, vz[kk][0], vs[kk][0]),
                                     dequant2(x2.x, x3.x, vz[kk][1], vs[kk][1]), dequant2(x2.y, x3.y, vz[kk][1], vs[kk][1]), pb[kk][0], pb[kk][1]);
                        }
                    }
                    if (i == kUnits) break;
                    __syncwarp();
                    if (lane == 0) mbar_arrive(bar_vempty + sv * 8);
                    red_inc_if(reporter, &g_prog[0]);
                    if (++sv == kStages) {
                        sv = 0;
                        phv ^= 1;
                    }
                }
#pragma unroll
                for (int m = 0; m < kNT; m++) {
                    acc[m][0] *= a0;
                    acc[m][1] *= a1;
                    acc[m][2] *= a0;
                    acc[m][3] *= a1;
                }
#pragma unroll
                for (int kk = 0; kk < 4; kk++) {
                    pb[kk][0] = pn[kk][0];
                    pb[kk][1] = pn[kk][1];
                }
            }
        }
        float o[2 * kNT];
#pragma unroll
        for (int m = 0; m < kNT; m++)
#pragma unroll
            for (int e = 0; e < 2; e++) {
                const float keep = hsel ? acc[m][2 * e + 1] : acc[m][2 * e];
                const float send = hsel ? acc[m][2 * e] : acc[m][2 * e + 1];
                o[2 * m + e] = keep + __shfl_xor_sync(0xffffffffu, send, 2);
            }
        if (kNT == 2) {
            st_relaxed4_if(pass && !merger, optr, make_uint4(tagged(o[0], tag), tagged(o[1], tag), tagged(o[2 * kNT - 2], tag), tagged(o[2 * kNT - 1], tag)));
            sts128f(osm, o[0], o[1], o[2 * kNT - 2], o[2 * kNT - 1]);
        } else {
            st_relaxed2_if(pass && !merger, optr, make_uint2(tagged(o[0], tag), tagged(o[1], tag)));
            sts64f(osm, o[0], o[1]);
        }
    }
    if (merger) asm volatile("bar.arrive 3, %0;" ::"n"(kThreads - 32) : "memory");
    red_inc_if(reporter, &g_prog[0]);
}

typedef CUresult (*EncodeTiledFn)(CUtensorMap*, CUtensorMapDataType, cuuint32_t, void*, const cuuint64_t*,
                                  const cuuint64_t*, const cuuint32_t*, const cuuint32_t*, CUtensorMapInterleave,
                                  CUtensorMapSwizzle, CUtensorMapL2promotion, CUtensorMapFloatOOBfill);

}

extern "C" void kernel_launch(void* const* d_in, const int* in_sizes, int n_in, void* d_out, int out_size) {
    (void)in_sizes;
    (void)n_in;
    (void)out_size;
    static EncodeTiledFn encode = nullptr;
    if (!encode) {
        cudaDriverEntryPointQueryResult qr;
        void* fn = nullptr;
        cudaGetDriverEntryPoint("cuTensorMapEncodeTiled", &fn, cudaEnableDefault, &qr);
        encode = (EncodeTiledFn)fn;
        cudaFuncSetAttribute(kivi_decode_kernel, cudaFuncAttributeMaxDynamicSharedMemorySize, kSmemBytes);
    }
    CUtensorMap map_v;
    const cuuint64_t gdim[4] = {32, 8, 4, (cuuint64_t)kBH * kS / 8};
    const cuuint64_t gstr[3] = {512, 128, 4096};
    const cuuint32_t box[4] = {32, 8, 4, kTok / 8};
    const cuuint32_t estr[4] = {1, 1, 1, 1};
    encode(&map_v, CU_TENSOR_MAP_DATA_TYPE_INT32, 4, d_in[2], gdim, gstr, box, estr, CU_TENSOR_MAP_INTERLEAVE_NONE,
           CU_TENSOR_MAP_SWIZZLE_128B, CU_TENSOR_MAP_L2_PROMOTION_NONE, CU_TENSOR_MAP_FLOAT_OOB_FILL_NONE);

    kivi_decode_kernel<<<kCtas, kThreads, kSmemBytes>>>(
        (const int*)d_in[1], (const __nv_bfloat16*)d_in[3], (const __nv_bfloat16*)d_in[4], (const __nv_bfloat16*)d_in[5],
        (const __nv_bfloat16*)d_in[6], (const __nv_bfloat16*)d_in[0], (__nv_bfloat16*)d_out, map_v);
}
```

```cpp
#include <cuda_runtime.h>
#include <cuda_bf16.h>
#include <cuda.h>
#include <stdint.h>
#include <float.h>

#define WARM 0
#define D0 7.0
#define D1 3.0
#define J0 8
#define J1 24
#define STAG 1
#define NC 4
#define POLL_AT 1
#define INIT_AT 56
#define PF 1
#define NSET 1
#define SETNS 120
#define SPIN 0

namespace {

constexpr int kB = 2, kHq = 32, kHkv = 8, kS = 32768, kD = 128, kG = 32;
constexpr int kRep = kHq / kHkv;
constexpr int kBH = kB * kHkv;
constexpr int kSplit = 8;
constexpr int kCtas = kBH * kSplit;
constexpr int kTok = 64;
constexpr int kUnitsPerBH = kS / kTok;
constexpr int kUnits = kUnitsPerBH / kSplit;
constexpr int kStages = 3;
constexpr int kVsRing = 8;
constexpr int kTile = kTok * kD * 4;
constexpr int kKsBytes = (kTok / kG) * kD * 2;
constexpr int kVsBytes = kTok * 2;
constexpr int kCW = NC;
constexpr int kNT = 8 / kCW;
constexpr int kThreads = (1 + kCW + 4 * NSET) * 32;
constexpr int kRow = kD + 8;
constexpr uint32_t kProgTotal = kCtas * 2 * kUnits;

constexpr int kOffK = 0;
constexpr int kOffV = kOffK + kStages * kTile;
constexpr int kOffKs = kOffV + kStages * kTile;
constexpr int kOffVs = kOffKs + kStages * 2 * kKsBytes;
constexpr int kOffSc = kOffVs + kVsRing * 2 * kVsBytes;
constexpr int kOffPart = kOffSc + 2 * 1024;
constexpr int kOffBar = kOffPart + kRep * kRow * 4;
constexpr int kOffTag = kOffBar + 4 * kStages * 8;
constexpr int kOffDone = kOffTag + 16;
constexpr int kSmemBytes = kOffDone + 16 + 1024;

__device__ __align__(128) uint32_t g_scratch[kCtas * kRep * kRow + 32];

#define TSTAMP(k)
#define TGET(v)
#define TPUT(k,v)

__device__ __forceinline__ uint32_t smem_u32(const void* p) { return (uint32_t)__cvta_generic_to_shared(p); }
__device__ __forceinline__ bool elect_one() {
    uint32_t p;
    asm volatile("{\n.reg .pred P;\nelect.sync _|P, 0xffffffff;\nselp.u32 %0, 1, 0, P;\n}" : "=r"(p));
    return p != 0;
}
__device__ __forceinline__ void mbar_init(uint32_t bar, uint32_t cnt) {
    asm volatile("mbarrier.init.shared::cta.b64 [%0], %1;" ::"r"(bar), "r"(cnt) : "memory");
}
__device__ __forceinline__ void mbar_expect_tx(uint32_t bar, uint32_t bytes) {
    asm volatile("mbarrier.arrive.expect_tx.shared::cta.b64 _, [%0], %1;" ::"r"(bar), "r"(bytes) : "memory");
}
__device__ __forceinline__ void mbar_arrive(uint32_t bar) {
    asm volatile("mbarrier.arrive.shared::cta.b64 _, [%0];" ::"r"(bar) : "memory");
}
__device__ __forceinline__ void mbar_wait(uint32_t bar, uint32_t parity) {
    uint32_t done;
    int it = 0;
    do {
        asm volatile(
            "{\n.reg .pred p;\nmbarrier.try_wait.parity.shared::cta.b64 p, [%1], %2;\nselp.u32 %0, 1, 0, p;\n}"
            : "=r"(done)
            : "r"(bar), "r"(parity)
            : "memory");
        if (++it > (1 << 24)) __trap();
    } while (!done);
}
__device__ __forceinline__ void mbar_spin(uint32_t bar, uint32_t parity) {
    uint32_t done;
    int it = 0;
    do {
        asm volatile(
            "{\n.reg .pred p;\nmbarrier.test_wait.parity.shared::cta.b64 p, [%1], %2;\nselp.u32 %0, 1, 0, p;\n}"
            : "=r"(done)
            : "r"(bar), "r"(parity)
            : "memory");
        if (++it > (1 << 26)) __trap();
    } while (!done);
}
__device__ __forceinline__ void bulk_load(uint32_t dst, const void* src, uint32_t bytes, uint32_t bar, uint64_t pol) {
    asm volatile(
        "cp.async.bulk.shared::cluster.global.mbarrier::complete_tx::bytes.L2::cache_hint [%0], [%1], %2, [%3], %4;" ::"r"(dst),
        "l"(src), "r"(bytes), "r"(bar), "l"(pol)
        : "memory");
}
__device__ __forceinline__ void tensor_load_4d(uint32_t dst, const CUtensorMap* m, int c3, uint32_t bar, uint64_t pol) {
    asm volatile(
        "cp.async.bulk.tensor.4d.shared::cluster.global.mbarrier::complete_tx::bytes.L2::cache_hint "
        "[%0], [%1, {%3, %3, %3, %4}], [%2], %5;" ::"r"(dst),
        "l"(m), "r"(bar), "r"(0), "r"(c3), "l"(pol)
        : "memory");
}
__device__ __forceinline__ int4 lds128(uint32_t a) {
    int4 v;
    asm volatile("ld.shared.v4.s32 {%0,%1,%2,%3}, [%4];" : "=r"(v.x), "=r"(v.y), "=r"(v.z), "=r"(v.w) : "r"(a));
    return v;
}
__device__ __forceinline__ float4 lds128f(uint32_t a) {
    float4 v;
    asm volatile("ld.shared.v4.f32 {%0,%1,%2,%3}, [%4];" : "=f"(v.x), "=f"(v.y), "=f"(v.z), "=f"(v.w) : "r"(a));
    return v;
}
__device__ __forceinline__ void sts128f(uint32_t a, float x, float y, float z, float w) {
    asm volatile("st.shared.v4.f32 [%0], {%1,%2,%3,%4};" ::"r"(a), "f"(x), "f"(y), "f"(z), "f"(w) : "memory");
}
__device__ __forceinline__ void sts64f(uint32_t a, float x, float y) {
    asm volatile("st.shared.v2.f32 [%0], {%1,%2};" ::"r"(a), "f"(x), "f"(y) : "memory");
}
__device__ __forceinline__ uint2 lds64(uint32_t a) {
    uint2 v;
    asm volatile("ld.shared.v2.u32 {%0,%1}, [%2];" : "=r"(v.x), "=r"(v.y) : "r"(a));
    return v;
}
__device__ __forceinline__ uint32_t lds32(uint32_t a) {
    uint32_t v;
    asm volatile("ld.shared.u32 %0, [%1];" : "=r"(v) : "r"(a));
    return v;
}
__device__ __forceinline__ uint32_t ld_relaxed(const unsigned int* p) {
    uint32_t v;
    asm volatile("ld.relaxed.gpu.global.u32 %0, [%1];" : "=r"(v) : "l"(p) : "memory");
    return v;
}
__device__ __forceinline__ uint4 ld_relaxed4(const uint32_t* p) {
    uint4 v;
    asm volatile("ld.relaxed.gpu.global.v4.u32 {%0,%1,%2,%3}, [%4];" : "=r"(v.x), "=r"(v.y), "=r"(v.z), "=r"(v.w) : "l"(p) : "memory");
    return v;
}
__device__ __forceinline__ uint2 ld_relaxed2(const uint32_t* p) {
    uint2 v;
    asm volatile("ld.relaxed.gpu.global.v2.u32 {%0,%1}, [%2];" : "=r"(v.x), "=r"(v.y) : "l"(p) : "memory");
    return v;
}
__device__ __forceinline__ void st_relaxed4(uint32_t* p, uint4 v) {
    asm volatile("st.relaxed.gpu.global.v4.u32 [%0], {%1,%2,%3,%4};" ::"l"(p), "r"(v.x), "r"(v.y), "r"(v.z), "r"(v.w) : "memory");
}
__device__ __forceinline__ void st_relaxed4_if(bool p_, uint32_t* p, uint4 v) {
    asm volatile("{\n.reg .pred P;\nsetp.ne.u32 P, %5, 0;\n@P st.relaxed.gpu.global.v4.u32 [%0], {%1,%2,%3,%4};\n}" ::"l"(p), "r"(v.x), "r"(v.y), "r"(v.z), "r"(v.w), "r"((uint32_t)p_) : "memory");
}
__device__ __forceinline__ void st_relaxed2_if(bool p_, uint32_t* p, uint2 v) {
    asm volatile("{\n.reg .pred P;\nsetp.ne.u32 P, %3, 0;\n@P st.relaxed.gpu.global.v2.u32 [%0], {%1,%2};\n}" ::"l"(p), "r"(v.x), "r"(v.y), "r"((uint32_t)p_) : "memory");
}
__device__ __forceinline__ void st_weak2_if(bool p_, void* p, uint2 v) {
    asm volatile("{\n.reg .pred P;\nsetp.ne.u32 P, %3, 0;\n@P st.global.v2.u32 [%0], {%1,%2};\n}" ::"l"(p), "r"(v.x), "r"(v.y), "r"((uint32_t)p_) : "memory");
}
__device__ __forceinline__ void red_inc_if(bool p_, unsigned int* p) {
    asm volatile("{\n.reg .pred P;\nsetp.ne.u32 P, %1, 0;\n@P red.relaxed.gpu.global.add.u32 [%0], 1;\n}" ::"l"(p), "r"((uint32_t)p_) : "memory");
}
__device__ __forceinline__ uint32_t pack_bf16(float lo, float hi) {
    uint32_t r;
    asm("cvt.rn.bf16x2.f32 %0, %1, %2;" : "=r"(r) : "f"(hi), "f"(lo));
    return r;
}
__device__ __forceinline__ uint32_t dequant2(int lo, int hi, uint32_t z, uint32_t s) {
    uint32_t x = pack_bf16(__int2float_rn(lo), __int2float_rn(hi));
    uint32_t r;
    asm("sub.rn.bf16x2 %0, %1, %2;" : "=r"(r) : "r"(x), "r"(z));
    asm("mul.rn.bf16x2 %0, %1, %2;" : "=r"(r) : "r"(r), "r"(s));
    return r;
}
__device__ __forceinline__ void mma_bf16(float (&c)[4], uint32_t a0, uint32_t a1, uint32_t a2, uint32_t a3, uint32_t b0,
                                         uint32_t b1) {
    asm("mma.sync.aligned.m16n8k16.row.col.f32.bf16.bf16.f32 {%0,%1,%2,%3}, {%4,%5,%6,%7}, {%8,%9}, {%0,%1,%2,%3};"
        : "+f"(c[0]), "+f"(c[1]), "+f"(c[2]), "+f"(c[3])
        : "r"(a0), "r"(a1), "r"(a2), "r"(a3), "r"(b0), "r"(b1));
}
__device__ __forceinline__ float ex2(float x) {
    float y;
    asm("ex2.approx.ftz.f32 %0, %1;" : "=f"(y) : "f"(x));
    return y;
}
__device__ __forceinline__ uint32_t tagged(float x, uint32_t tag) { return (__float_as_uint(x) & ~1u) | tag; }
__device__ __forceinline__ uint32_t split_p(float a, float b, bool lo) {
    uint32_t h = pack_bf16(a, b);
    if (lo) h = pack_bf16(a - __uint_as_float(h << 16), b - __uint_as_float(h & 0xffff0000u));
    return h;
}
__device__ __forceinline__ uint32_t pin(uint32_t x) { return __shfl_sync(0xffffffffu, x, threadIdx.x & 31); }
template <typename T>
__device__ __forceinline__ T* pin(T* p) {
    const uint64_t a = reinterpret_cast<uint64_t>(p);
    return reinterpret_cast<T*>((uint64_t)pin((uint32_t)(a >> 32)) << 32 | pin((uint32_t)a));
}

__global__ void __launch_bounds__(kThreads, 1)
kivi_decode_kernel(const int* __restrict__ qk, const int* __restrict__ qv, const __nv_bfloat16* __restrict__ k_scales,
                   const __nv_bfloat16* __restrict__ k_zeros, const __nv_bfloat16* __restrict__ v_scales,
                   const __nv_bfloat16* __restrict__ v_zeros, const __nv_bfloat16* __restrict__ q,
                   __nv_bfloat16* __restrict__ out, uint32_t* __restrict__ g_part, unsigned int* __restrict__ g_prog,
                   const __grid_constant__ CUtensorMap map_v) {
    extern __shared__ uint8_t smem_raw[];
    unsigned long long t0 = 0, t1 = 0, t2 = 0;
    TGET(t0);
    const uint32_t sb = (smem_u32(smem_raw) + 1023u) & ~1023u;
    const uint32_t bar_kfull = sb + kOffBar;
    const uint32_t bar_kempty = bar_kfull + kStages * 8;
    const uint32_t bar_vempty = bar_kempty + kStages * 8;
    const uint32_t bar_vfull = bar_vempty + kStages * 8;
    constexpr uint32_t kKTx = kTile + 2 * kKsBytes + 2 * kVsBytes;

    const int bh = blockIdx.x / kSplit, r = blockIdx.x % kSplit;
    const int unit0 = bh * kUnitsPerBH + r;
    uint64_t pol;
    asm volatile("createpolicy.fractional.L2::evict_first.b64 %0, 1.0;" : "=l"(pol));
    const char* gk = reinterpret_cast<const char*>(qk);

    if (PF >= 1) asm volatile("prefetch.global.L2 [%0];" ::"l"(gk + (size_t)unit0 * kTile + (threadIdx.x & 255) * 128) : "memory");
    if (PF == 3 || PF == 4) asm volatile("prefetch.global.L2 [%0];" ::"l"((const char*)qv + (size_t)unit0 * kTile + (threadIdx.x & 255) * 128) : "memory");
    if (PF == 5) asm volatile("prefetch.global.L2 [%0];" ::"l"(gk + (size_t)(unit0 + kSplit) * kTile + (threadIdx.x & 255) * 128) : "memory");
    if ((PF == 2 || PF == 4 || PF == 5) && threadIdx.x >= 256) {
        const int l = threadIdx.x & 31;
        const char* p = l < 8    ? (const char*)qv + (size_t)unit0 * kTile + l * 128
                        : l < 12 ? (const char*)k_scales + (size_t)unit0 * kKsBytes + (l & 3) * 128
                        : l < 16 ? (const char*)k_zeros + (size_t)unit0 * kKsBytes + (l & 3) * 128
                        : l < 24 ? (const char*)v_scales + (size_t)unit0 * kVsBytes
                                 : (const char*)v_zeros + (size_t)unit0 * kVsBytes;
        asm volatile("prefetch.global.L2 [%0];" ::"l"(p) : "memory");
        if (l == 0) asm volatile("prefetch.tensormap [%0];" ::"l"(&map_v) : "memory");
    }
    if (threadIdx.x < 32) {
        if (elect_one()) {
            mbar_init(bar_kfull, 1);
            asm volatile("fence.mbarrier_init.release.cluster;" ::: "memory");
            mbar_expect_tx(bar_kfull, kKTx);
            bulk_load(sb + kOffK, gk + (size_t)unit0 * kTile, kTile, bar_kfull, pol);
            TGET(t1);
        }
        __syncwarp();
    }

    const int warp = __shfl_sync(0xffffffffu, threadIdx.x >> 5, 0), lane = threadIdx.x & 31;
    const bool merger = (r == kSplit - 1);

    if (warp == 0 || warp > kCW) {
        if (warp == 0) {
            const char* gks = reinterpret_cast<const char*>(k_scales);
            const char* gkz = reinterpret_cast<const char*>(k_zeros);
            const char* gvs = reinterpret_cast<const char*>(v_scales);
            const char* gvz = reinterpret_cast<const char*>(v_zeros);
            auto issue_scales = [&](int i, int s) {
                const int u = unit0 + i * kSplit;
                const uint32_t bar = bar_kfull + s * 8;
                const uint32_t vsd = sb + kOffVs + (i & (kVsRing - 1)) * 2 * kVsBytes;
                bulk_load(sb + kOffKs + s * 2 * kKsBytes, gks + (size_t)u * kKsBytes, kKsBytes, bar, pol);
                bulk_load(sb + kOffKs + s * 2 * kKsBytes + kKsBytes, gkz + (size_t)u * kKsBytes, kKsBytes, bar, pol);
                bulk_load(vsd, gvs + (size_t)u * kVsBytes, kVsBytes, bar, pol);
                bulk_load(vsd + kVsBytes, gvz + (size_t)u * kVsBytes, kVsBytes, bar, pol);
            };
            if (elect_one()) {
                asm volatile("prefetch.tensormap [%0];" ::"l"(&map_v) : "memory");
                issue_scales(0, 0);
#pragma unroll
                for (int s = 0; s < kStages; s++) {
                    if (s) mbar_init(bar_kfull + s * 8, 1);
                    mbar_init(bar_kempty + s * 8, kCW);
                    mbar_init(bar_vempty + s * 8, kCW);
                    mbar_init(bar_vfull + s * 8, 1);
                }
                asm volatile("fence.mbarrier_init.release.cluster;" ::: "memory");
            }
            __syncwarp();
            asm volatile("bar.arrive 0, %0;" ::"n"(32 + kCW * 32) : "memory");
            if (elect_one()) {
                const int stag = STAG == 0   ? 0
                                 : STAG == 1 ? (int)(__brev(blockIdx.x) >> 25) - 64
                                 : STAG == 2 ? (merger ? 32 : 0)
                                 : STAG == 3 ? (merger ? 64 : 0)
                                             : (merger ? 64 + bh : (r * 16 + bh) / 2 - 32);
                uint32_t seen = 0;
                bool pace = true;
                auto throttle = [&](int j) {
                    constexpr int d0 = (int)(D0 * kCtas), d1 = (int)(D1 * kCtas);
                    const int dj = j <= J0 ? d0 : j >= J1 ? d1 : d0 + (d1 - d0) * (j - J0) / (J1 - J0);
                    const int need = (j + 1) * kCtas - dj + stag;
                    int it = 0;
                    while (pace && (int)seen < need) {
                        seen = ld_relaxed(&g_prog[0]) & (kProgTotal - 1);
                        if (++it > 128) pace = false;
                    }
                };
                int s = 0;
                uint32_t ph = 1;
#pragma unroll 1
                for (int i = 0; i < kUnits; i++) {
                    int s1 = s + 1;
                    uint32_t ph1 = ph;
                    if (s1 == kStages) {
                        s1 = 0;
                        ph1 ^= 1;
                    }
                    if (i + 1 < kUnits) {
                        throttle(2 * i + 1);
                        mbar_wait(bar_kempty + s1 * 8, ph1);
                        mbar_expect_tx(bar_kfull + s1 * 8, kKTx);
                        bulk_load(sb + kOffK + s1 * kTile, gk + (size_t)(unit0 + (i + 1) * kSplit) * kTile, kTile, bar_kfull + s1 * 8, pol);
                        issue_scales(i + 1, s1);
                    }
                    throttle(i + 1 < kUnits ? 2 * i + 2 : 2 * i + 1);
                    mbar_wait(bar_vempty + s * 8, ph);
                    mbar_expect_tx(bar_vfull + s * 8, kTile);
                    tensor_load_4d(sb + kOffV + s * kTile, &map_v, (unit0 + i * kSplit) * (kTok / 8), bar_vfull + s * 8, pol);
                    if (i == 1) TGET(t2);
                    if (i == 8) {
                        const uint32_t tag = ((ld_relaxed(&g_prog[0]) / kProgTotal) & 1) ^ 1;
                        asm volatile("st.shared.u32 [%0], %1;" ::"r"(sb + kOffTag), "r"(tag) : "memory");
                        sts128f(sb + kOffDone, 0.f, 0.f, 0.f, 0.f);
                    }
                    s = s1;
                    ph = ph1;
                }
                TPUT(0, t0); TPUT(1, t1); TPUT(2, t2);
            }
            return;
        }
        if (!merger) return;
        const int head = (warp - kCW - 1) & 3, hset = (warp - kCW - 1) >> 2;
        const uint32_t* row = pin(g_part + (size_t)(bh * kSplit * kRep + head) * kRow + lane * 4);
        const uint32_t* mlp = g_part + (size_t)((bh * kSplit + (lane & 7)) * kRep + head) * kRow + kD;
        __nv_bfloat16* optr = pin(out + (size_t)(bh * kRep + head) * kD + lane * 4);
        const uint32_t own = pin(sb + kOffPart + (head * kRow + lane * 4) * 4);
        const bool tsl = threadIdx.x == (kCW + 1) * 32;
#pragma unroll 1
        for (int pass = WARM ? 0 : 1; pass < 2; pass++) {
            if (pass) asm volatile("bar.sync 2, %0;" ::"n"(32 + 128 * NSET) : "memory");
            if (NSET > 1 && hset) __nanosleep(hset * SETNS);
            const uint32_t tag = pass ? lds32(sb + kOffTag) : 0;
            uint2 w = lds64(sb + kOffPart + (head * kRow + kD) * 4);
            uint4 v[kSplit - 1];
#pragma unroll
            for (int k = 0; k < kSplit - 1; k++) v[k] = make_uint4(0, 0, 0, 0);
            float wt[kSplit];
            bool have_w = false;
            bool ok = !pass || (lane & 7) == kSplit - 1;
            uint32_t pending = pass ? (1u << (kSplit - 1)) - 1 : 0;
            int it = 0;
            do {
#pragma unroll
                for (int k = 0; k < kSplit - 1; k++)
                    if (pending >> k & 1) v[k] = ld_relaxed4(row + k * (kRep * kRow));
                if (!have_w) {
                    if (!ok) {
                        w = ld_relaxed2(mlp);
                        ok = (((w.x ^ tag) | (w.y ^ tag)) & 1) == 0;
                    }
                    if (__all_sync(0xffffffffu, ok)) {
                        have_w = true;
                        const float mk = __uint_as_float(w.x), lk = __uint_as_float(w.y);
                        float M = fmaxf(mk, __shfl_xor_sync(0xffffffffu, mk, 1));
                        M = fmaxf(M, __shfl_xor_sync(0xffffffffu, M, 2));
                        M = fmaxf(M, __shfl_xor_sync(0xffffffffu, M, 4));
                        float wk = ex2(mk - M);
                        float L = wk * lk;
                        L += __shfl_xor_sync(0xffffffffu, L, 1);
                        L += __shfl_xor_sync(0xffffffffu, L, 2);
                        L += __shfl_xor_sync(0xffffffffu, L, 4);
                        wk = wk / L;
#pragma unroll
                        for (int k = 0; k < kSplit; k++) wt[k] = __shfl_sync(0xffffffffu, wk, k);
                        if (pass && tsl) TSTAMP(13);
                    }
                }
                uint32_t bad = have_w ? 0 : 0x80;
#pragma unroll
                for (int k = 0; k < kSplit - 1; k++)
                    bad |= ((((v[k].x ^ tag) | (v[k].y ^ tag)) | ((v[k].z ^ tag) | (v[k].w ^ tag))) & 1) << k;
                pending = __reduce_or_sync(0xffffffffu, bad);
                if (++it > (1 << 22)) __trap();
            } while (pending);
            if (pass) TGET(t1);
            if (NSET > 1) {
                if (lds32(sb + kOffDone + head * 4)) return;
                asm volatile("st.shared.u32 [%0], %1;" ::"r"(sb + kOffDone + head * 4), "r"(1) : "memory");
            }
            float4 o = make_float4(0.f, 0.f, 0.f, 0.f);
#pragma unroll
            for (int k = 0; k < kSplit - 1; k++) {
                o.x += wt[k] * __uint_as_float(v[k].x);
                o.y += wt[k] * __uint_as_float(v[k].y);
                o.z += wt[k] * __uint_as_float(v[k].z);
                o.w += wt[k] * __uint_as_float(v[k].w);
            }
            if (pass) asm volatile("bar.sync %0, %1;" ::"r"(3 + hset * 4 + head), "n"(kCW * 32 + 32) : "memory");
            const float4 cv = lds128f(own);
            uint2 res;
            res.x = pack_bf16(o.x + wt[kSplit - 1] * cv.x, o.y + wt[kSplit - 1] * cv.y);
            res.y = pack_bf16(o.z + wt[kSplit - 1] * cv.z, o.w + wt[kSplit - 1] * cv.w);
            st_weak2_if(pass, optr, res);
        }
        if (tsl) { TSTAMP(11); TPUT(14, t1); }
        return;
    }

    const int cw = warp - 1;
    const int g = lane >> 2, c = lane & 3;
    const int par = g & 1;
    uint2 qf[4][2];
    {
        const __nv_bfloat16* qrow = q + (size_t)(bh * kRep + (g & 3)) * kD + 4 * c;
#pragma unroll
        for (int P = 0; P < 4; P++) {
            qf[P][0] = __ldg(reinterpret_cast<const uint2*>(qrow + 32 * P));
            qf[P][1] = __ldg(reinterpret_cast<const uint2*>(qrow + 32 * P + 16));
        }
    }
    const uint32_t k_lane0 = sb + kOffK + (8 * kNT * cw + g) * 512 + c * 16 + par * 64;
    const uint32_t ks_lane0 = sb + kOffKs + (cw * kNT / 4) * (kD * 2) + c * 8 + par * 32;
    const int vchunk = kNT == 2 ? g : (cw & 1) * 4 + (g >> 1);
    const uint32_t v_lane0 = pin(sb + kOffV + (cw * kNT / 2) * 1024 + (2 * c) * 128 + ((vchunk ^ (2 * c)) * 16) + (kNT == 2 ? 0 : (g & 1) * 8));
    const uint32_t vs_lane = sb + kOffVs + (2 * c) * 2;
    const uint32_t sc_rd = sb + kOffSc + ((g & 3) * 4 + c) * 16;
    const uint32_t sc_wr = sc_rd + (cw * kNT / 2) * 256 + (kNT == 2 ? 0 : (cw & 1) * 8);
    const int hsel = c >> 1;
    const int ocol = (2 * (c & 1) + hsel) * kRow + 16 * kNT * cw + 2 * kNT * g;
    uint32_t* optr = pin(g_part + (size_t)blockIdx.x * kRep * kRow + ocol);
    const uint32_t osm = pin(sb + kOffPart + ocol * 4);
    const bool reporter = threadIdx.x == 32;

    const float sl2e = 0.08838834764831845f * 1.4426950408889634f;
    float acc[kNT][4];
#pragma unroll
    for (int m = 0; m < kNT; m++)
#pragma unroll
        for (int e = 0; e < 4; e++) acc[m][e] = 0.f;
    float m_run = -FLT_MAX, l_run = 0.f;
    uint32_t tag = 0;

#pragma unroll 1
    for (int pass = WARM ? 0 : 1; pass < 2; pass++) {
        if (pass) {
            asm volatile("bar.sync 0, %0;" ::"n"(32 + kCW * 32) : "memory");
            int sk = 0, sv = 0;
            uint32_t phk = 0, phv = 0;
            uint32_t pb[4][2];
#pragma unroll
            for (int k = 0; k < 4; k++) pb[k][0] = pb[k][1] = 0;
#pragma unroll 1
            for (int i = 0; i <= kUnits; i++) {
                uint32_t pn[4][2];
                float a0 = 1.f, a1 = 1.f;
                if (i < kUnits) {
                    mbar_wait(bar_kfull + sk * 8, phk);
                    if (threadIdx.x == 32 && i == 0) TSTAMP(3);
                    if (threadIdx.x == 32 && i == kUnits - 1) TSTAMP(4);
                    float sa[kNT][2][4];
#pragma unroll
                    for (int u = 0; u < kNT; u++)
#pragma unroll
                        for (int e = 0; e < 2; e++)
#pragma unroll
                            for (int k = 0; k < 4; k++) sa[u][e][k] = 0.f;
#pragma unroll
                    for (int P = 0; P < 4; P++)
#pragma unroll
                        for (int e = 0; e < 2; e++) {
                            const uint32_t ka = (k_lane0 ^ (e * 64)) + sk * kTile + P * 128;
                            const uint32_t sa_ = (ks_lane0 ^ (e * 32)) + sk * (2 * kKsBytes) + P * 64;
                            const uint2 zr = lds64(sa_ + kKsBytes);
                            const uint2 sc = lds64(sa_);
#pragma unroll
                            for (int u = 0; u < kNT; u++) {
                                const int4 x = lds128(ka + u * 8 * 512);
                                mma_bf16(sa[u][e], qf[P][e].x, qf[P][e ^ 1].x, qf[P][e].y, qf[P][e ^ 1].y,
                                         dequant2(x.x, x.y, zr.x, sc.x), dequant2(x.z, x.w, zr.y, sc.y));
                            }
                        }
                    __syncwarp();
                    if (lane == 0) mbar_arrive(bar_kempty + sk * 8);
                    red_inc_if(reporter, &g_prog[0]);
                    if (g < 4) {
                        if (kNT == 2)
                            sts128f(sc_wr + (i & 1) * 1024, (sa[0][0][0] + sa[0][1][0]) * sl2e, (sa[0][0][3] + sa[0][1][3]) * sl2e,
                                    (sa[kNT - 1][0][0] + sa[kNT - 1][1][0]) * sl2e, (sa[kNT - 1][0][3] + sa[kNT - 1][1][3]) * sl2e);
                        else
                            sts64f(sc_wr + (i & 1) * 1024, (sa[0][0][0] + sa[0][1][0]) * sl2e, (sa[0][0][3] + sa[0][1][3]) * sl2e);
                    }
                    if (++sk == kStages) {
                        sk = 0;
                        phk ^= 1;
                    }
                    asm volatile("bar.sync 1, %0;" ::"n"(kCW * 32) : "memory");
                    float4 t[4];
#pragma unroll
                    for (int kk = 0; kk < 4; kk++) t[kk] = lds128f(sc_rd + (i & 1) * 1024 + kk * 256);
                    float mx = m_run;
#pragma unroll
                    for (int kk = 0; kk < 4; kk++) mx = fmaxf(mx, fmaxf(fmaxf(t[kk].x, t[kk].y), fmaxf(t[kk].z, t[kk].w)));
                    mx = fmaxf(mx, __shfl_xor_sync(0xffffffffu, mx, 1));
                    mx = fmaxf(mx, __shfl_xor_sync(0xffffffffu, mx, 2));
                    const float alpha = ex2(m_run - mx);
                    m_run = mx;
                    a0 = __shfl_sync(0xffffffffu, alpha, ((2 * c) & 3) * 4);
                    a1 = __shfl_sync(0xffffffffu, alpha, ((2 * c + 1) & 3) * 4);
                    float ls = 0.f;
#pragma unroll
                    for (int kk = 0; kk < 4; kk++) {
                        const float p0 = ex2(t[kk].x - mx), p1 = ex2(t[kk].y - mx), p2 = ex2(t[kk].z - mx), p3 = ex2(t[kk].w - mx);
                        ls += (p0 + p1) + (p2 + p3);
                        pn[kk][0] = split_p(p0, p1, g >= 4);
                        pn[kk][1] = split_p(p2, p3, g >= 4);
                    }
                    l_run = l_run * alpha + ls;
                    if (i == INIT_AT) {
                        tag = lds32(sb + kOffTag);
                        const uint32_t nt = tag ^ 1;
                        if (kNT == 2) st_relaxed4_if(!merger, optr, make_uint4(nt, nt, nt, nt));
                        else st_relaxed2_if(!merger, optr, make_uint2(nt, nt));
                        st_relaxed4_if(!merger && cw == 0 && g < 4 && c < 2, g_part + (size_t)(blockIdx.x * kRep + (g & 3)) * kRow + kD + (c & 1) * 4, make_uint4(nt, nt, nt, nt));
                    }
                    if (i == kUnits - 1) {
                        if (INIT_AT >= kUnits) tag = lds32(sb + kOffTag);
                        if (cw == 0) {
                            float l = l_run + __shfl_xor_sync(0xffffffffu, l_run, 1);
                            l += __shfl_xor_sync(0xffffffffu, l, 2);
                            if (g < 4 && c < 2) {
                                if (merger)
                                    sts128f(sb + kOffPart + (g * kRow + kD + c * 4) * 4, m_run, l, m_run, l);
                                else
                                    st_relaxed4(g_part + (size_t)(blockIdx.x * kRep + g) * kRow + kD + c * 4,
                                                make_uint4(tagged(m_run, tag), tagged(l, tag), 0, 0));
                            }
                            if (merger) asm volatile("bar.arrive 2, %0;" ::"n"(32 + 128 * NSET) : "memory");
                        }
                    }
                }
                if (i > 0) {
                    const uint32_t va0 = v_lane0 + sv * kTile, va1 = va0 ^ (128 + 16);
                    const uint32_t vsb = vs_lane + ((i - 1) & (kVsRing - 1)) * (2 * kVsBytes);
                    uint32_t vs[4][2], vz[4][2];
#pragma unroll
                    for (int kk = 0; kk < 4; kk++)
#pragma unroll
                        for (int u = 0; u < 2; u++) {
                            vs[kk][u] = lds32(vsb + kk * 32 + u * 16);
                            vz[kk][u] = lds32(vsb + kVsBytes + kk * 32 + u * 16);
                        }
                    if (SPIN) mbar_spin(bar_vfull + sv * 8, phv); else mbar_wait(bar_vfull + sv * 8, phv);
                    if (threadIdx.x == 32 && i == kUnits) TGET(t1);
#pragma unroll
                    for (int kk = 0; kk < 4; kk++) {
                        if (kNT == 2) {
                            const int4 x0 = lds128(va0 + kk * 8192);
                            const int4 x1 = lds128(va1 + kk * 8192);
                            const int4 x2 = lds128(va0 + kk * 8192 + 4096);
                            const int4 x3 = lds128(va1 + kk * 8192 + 4096);
                            mma_bf16(acc[0], dequant2(x0.x, x1.x, vz[kk][0], vs[kk][0]), dequant2(x0.y, x1.y, vz[kk][0], vs[kk][0]),
                                     dequant2(x2.x, x3.x, vz[kk][1], vs[kk][1]), dequant2(x2.y, x3.y, vz[kk][1], vs[kk][1]), pb[kk][0], pb[kk][1]);
                            mma_bf16(acc[kNT - 1], dequant2(x0.z, x1.z, vz[kk][0], vs[kk][0]), dequant2(x0.w, x1.w, vz[kk][0], vs[kk][0]),
                                     dequant2(x2.z, x3.z, vz[kk][1], vs[kk][1]), dequant2(x2.w, x3.w, vz[kk][1], vs[kk][1]), pb[kk][0], pb[kk][1]);
                        } else {
                            const uint2 x0 = lds64(va0 + kk * 8192);
                            const uint2 x1 = lds64(va1 + kk * 8192);
                            const uint2 x2 = lds64(va0 + kk * 8192 + 4096);
                            const uint2 x3 = lds64(va1 + kk * 8192 + 4096);
                            mma_bf16(acc[0], dequant2(x0.x, x1.x, vz[kk][0], vs[kk][0]), dequant2(x0.y, x1.y, vz[kk][0], vs[kk][0]),
                                     dequant2(x2.x, x3.x, vz[kk][1], vs[kk][1]), dequant2(x2.y, x3.y, vz[kk][1], vs[kk][1]), pb[kk][0], pb[kk][1]);
                        }
                    }
                    if (i == kUnits) break;
                    __syncwarp();
                    if (lane == 0) mbar_arrive(bar_vempty + sv * 8);
                    red_inc_if(reporter, &g_prog[0]);
                    if (++sv == kStages) {
                        sv = 0;
                        phv ^= 1;
                    }
                }
#pragma unroll
                for (int m = 0; m < kNT; m++) {
                    acc[m][0] *= a0;
                    acc[m][1] *= a1;
                    acc[m][2] *= a0;
                    acc[m][3] *= a1;
                }
#pragma unroll
                for (int kk = 0; kk < 4; kk++) {
                    pb[kk][0] = pn[kk][0];
                    pb[kk][1] = pn[kk][1];
                }
            }
        }
        float o[2 * kNT];
#pragma unroll
        for (int m = 0; m < kNT; m++)
#pragma unroll
            for (int e = 0; e < 2; e++) {
                const float keep = hsel ? acc[m][2 * e + 1] : acc[m][2 * e];
                const float send = hsel ? acc[m][2 * e] : acc[m][2 * e + 1];
                o[2 * m + e] = keep + __shfl_xor_sync(0xffffffffu, send, 2);
            }
        if (kNT == 2) {
            st_relaxed4_if(pass && !merger, optr, make_uint4(tagged(o[0], tag), tagged(o[1], tag), tagged(o[2 * kNT - 2], tag), tagged(o[2 * kNT - 1], tag)));
            sts128f(osm, o[0], o[1], o[2 * kNT - 2], o[2 * kNT - 1]);
        } else {
            st_relaxed2_if(pass && !merger, optr, make_uint2(tagged(o[0], tag), tagged(o[1], tag)));
            sts64f(osm, o[0], o[1]);
        }
    }
    if (merger) {
#pragma unroll
        for (int k = 0; k < 4 * NSET; k++) asm volatile("bar.arrive %0, %1;" ::"r"(3 + k), "n"(kCW * 32 + 32) : "memory");
    }
    red_inc_if(reporter, &g_prog[0]);
}

typedef CUresult (*EncodeTiledFn)(CUtensorMap*, CUtensorMapDataType, cuuint32_t, void*, const cuuint64_t*,
                                  const cuuint64_t*, const cuuint32_t*, const cuuint32_t*, CUtensorMapInterleave,
                                  CUtensorMapSwizzle, CUtensorMapL2promotion, CUtensorMapFloatOOBfill);

}

extern "C" void kernel_launch(void* const* d_in, const int* in_sizes, int n_in, void* d_out, int out_size) {
    (void)in_sizes;
    (void)n_in;
    (void)out_size;
    static EncodeTiledFn encode = nullptr;
    static uint32_t* scratch = nullptr;
    if (!encode) {
        cudaGetSymbolAddress((void**)&scratch, g_scratch);
        cudaDriverEntryPointQueryResult qr;
        void* fn = nullptr;
        cudaGetDriverEntryPoint("cuTensorMapEncodeTiled", &fn, cudaEnableDefault, &qr);
        encode = (EncodeTiledFn)fn;
        cudaFuncSetAttribute(kivi_decode_kernel, cudaFuncAttributeMaxDynamicSharedMemorySize, kSmemBytes);
    }
    CUtensorMap map_v;
    const cuuint64_t gdim[4] = {32, 8, 4, (cuuint64_t)kBH * kS / 8};
    const cuuint64_t gstr[3] = {512, 128, 4096};
    const cuuint32_t box[4] = {32, 8, 4, kTok / 8};
    const cuuint32_t estr[4] = {1, 1, 1, 1};
    encode(&map_v, CU_TENSOR_MAP_DATA_TYPE_INT32, 4, d_in[2], gdim, gstr, box, estr, CU_TENSOR_MAP_INTERLEAVE_NONE,
           CU_TENSOR_MAP_SWIZZLE_128B, CU_TENSOR_MAP_L2_PROMOTION_NONE, CU_TENSOR_MAP_FLOAT_OOB_FILL_NONE);

    kivi_decode_kernel<<<kCtas, kThreads, kSmemBytes>>>(
        (const int*)d_in[1], (const int*)d_in[2], (const __nv_bfloat16*)d_in[3], (const __nv_bfloat16*)d_in[4], (const __nv_bfloat16*)d_in[5],
        (const __nv_bfloat16*)d_in[6], (const __nv_bfloat16*)d_in[0], (__nv_bfloat16*)d_out, scratch, scratch + kCtas * kRep * kRow, map_v);
}
```

```cpp
#include <cuda_runtime.h>
#include <cuda_bf16.h>
#include <cuda.h>
#include <stdint.h>
#include <float.h>

#define D0 7.0
#define D1 3.0
#define J0 8
#define J1 24
#define STAG 3
#define INIT_AT 54
#define PROMO 3
#define NEND 3
#define PF 1
#define CAP 64
#define SE 14
#define SG 22
#define K1TOP 0
#define FINLATE 1
#define PSLEEP 0
#define JA 125
#define JB 127
#define LSPLIT 0
#define LEARLY 32
#define FADE 0
#define E127 0
#define E126 0
#define SPIN 0

namespace {

constexpr int kB = 2, kHq = 32, kHkv = 8, kS = 32768, kD = 128, kG = 32;
constexpr int kRep = kHq / kHkv;
constexpr int kBH = kB * kHkv;
constexpr int kSplit = 8;
constexpr int kCtas = kBH * kSplit;
constexpr int kTok = 64;
constexpr int kUnitsPerBH = kS / kTok;
constexpr int kUnits = kUnitsPerBH / kSplit;
constexpr int kEnd = NEND;
constexpr int kMain = kUnits - kEnd;
constexpr int kStages = 3;
constexpr int kVsRing = 8;
constexpr int kTile = kTok * kD * 4;
constexpr int kKsBytes = (kTok / kG) * kD * 2;
constexpr int kVsBytes = kTok * 2;
constexpr int kVsEndBytes = kEnd * kSplit * kVsBytes;
constexpr int kCW = 4;
constexpr int kThreads = (2 + kCW) * 32;
constexpr uint32_t kProgTotal = kCtas * 2 * kUnits;
constexpr int kXo = 0, kXp = kRep * kD, kXm = kXp + kEnd * 256, kXWords = kXm + 32;

constexpr int kOffK = 0;
constexpr int kOffV = kOffK + kStages * kTile;
constexpr int kOffKs = kOffV + kStages * kTile;
constexpr int kOffVs = kOffKs + kStages * 2 * kKsBytes;
constexpr int kOffVsEnd = kOffVs + kVsRing * 2 * kVsBytes;
constexpr int kOffSc = kOffVsEnd + 2 * kVsEndBytes;
constexpr int kOffRed = kOffSc + 4 * 1024;
constexpr int kOffBar = kOffRed + kCW * 512;
constexpr int kOffTag = kOffBar + 4 * kStages * 8 + 32;
constexpr int kSmemBytes = kOffTag + 16 + 1024;

__device__ __align__(128) uint32_t g_scratch[kCtas * kXWords + 32];

#define TSTAMP(k)
#define TGET(v)
#define TPUT(k,v)

__device__ __forceinline__ uint32_t smem_u32(const void* p) { return (uint32_t)__cvta_generic_to_shared(p); }
__device__ __forceinline__ bool elect_one() {
    uint32_t p;
    asm volatile("{\n.reg .pred P;\nelect.sync _|P, 0xffffffff;\nselp.u32 %0, 1, 0, P;\n}" : "=r"(p));
    return p != 0;
}
__device__ __forceinline__ void mbar_init(uint32_t bar, uint32_t cnt) {
    asm volatile("mbarrier.init.shared::cta.b64 [%0], %1;" ::"r"(bar), "r"(cnt) : "memory");
}
__device__ __forceinline__ void mbar_expect_tx(uint32_t bar, uint32_t bytes) {
    asm volatile("mbarrier.arrive.expect_tx.shared::cta.b64 _, [%0], %1;" ::"r"(bar), "r"(bytes) : "memory");
}
__device__ __forceinline__ void mbar_arrive(uint32_t bar) {
    asm volatile("mbarrier.arrive.shared::cta.b64 _, [%0];" ::"r"(bar) : "memory");
}
__device__ __forceinline__ void mbar_wait(uint32_t bar, uint32_t parity) {
    uint32_t done;
    int it = 0;
    do {
        asm volatile(
            "{\n.reg .pred p;\nmbarrier.try_wait.parity.shared::cta.b64 p, [%1], %2;\nselp.u32 %0, 1, 0, p;\n}"
            : "=r"(done)
            : "r"(bar), "r"(parity)
            : "memory");
        if (++it > (1 << 24)) __trap();
    } while (!done);
}
__device__ __forceinline__ void mbar_spin(uint32_t bar, uint32_t parity) {
    uint32_t done;
    int it = 0;
    do {
        asm volatile(
            "{\n.reg .pred p;\nmbarrier.test_wait.parity.shared::cta.b64 p, [%1], %2;\nselp.u32 %0, 1, 0, p;\n}"
            : "=r"(done)
            : "r"(bar), "r"(parity)
            : "memory");
        if (++it > (1 << 26)) __trap();
    } while (!done);
}
__device__ __forceinline__ void bulk_load(uint32_t dst, const void* src, uint32_t bytes, uint32_t bar, uint64_t pol) {
    asm volatile(
        "cp.async.bulk.shared::cluster.global.mbarrier::complete_tx::bytes.L2::cache_hint [%0], [%1], %2, [%3], %4;" ::"r"(dst),
        "l"(src), "r"(bytes), "r"(bar), "l"(pol)
        : "memory");
}
__device__ __forceinline__ void tensor_load_4d(uint32_t dst, const CUtensorMap* m, int c0, int c3, uint32_t bar, uint64_t pol) {
    asm volatile(
        "cp.async.bulk.tensor.4d.shared::cluster.global.mbarrier::complete_tx::bytes.L2::cache_hint "
        "[%0], [%1, {%6, %3, %3, %4}], [%2], %5;" ::"r"(dst),
        "l"(m), "r"(bar), "r"(0), "r"(c3), "l"(pol), "r"(c0)
        : "memory");
}
__device__ __forceinline__ void tensor_load_5d(uint32_t dst, const CUtensorMap* m, int c0, int c3, int c4, uint32_t bar, uint64_t pol) {
    asm volatile(
        "cp.async.bulk.tensor.5d.shared::cluster.global.mbarrier::complete_tx::bytes.L2::cache_hint "
        "[%0], [%1, {%6, %3, %3, %4, %7}], [%2], %5;" ::"r"(dst),
        "l"(m), "r"(bar), "r"(0), "r"(c3), "l"(pol), "r"(c0), "r"(c4)
        : "memory");
}
__device__ __forceinline__ int4 lds128(uint32_t a) {
    int4 v;
    asm volatile("ld.shared.v4.s32 {%0,%1,%2,%3}, [%4];" : "=r"(v.x), "=r"(v.y), "=r"(v.z), "=r"(v.w) : "r"(a));
    return v;
}
__device__ __forceinline__ float4 lds128f(uint32_t a) {
    float4 v;
    asm volatile("ld.shared.v4.f32 {%0,%1,%2,%3}, [%4];" : "=f"(v.x), "=f"(v.y), "=f"(v.z), "=f"(v.w) : "r"(a));
    return v;
}
__device__ __forceinline__ void sts128f(uint32_t a, float x, float y, float z, float w) {
    asm volatile("st.shared.v4.f32 [%0], {%1,%2,%3,%4};" ::"r"(a), "f"(x), "f"(y), "f"(z), "f"(w) : "memory");
}
__device__ __forceinline__ void sts64f(uint32_t a, float x, float y) {
    asm volatile("st.shared.v2.f32 [%0], {%1,%2};" ::"r"(a), "f"(x), "f"(y) : "memory");
}
__device__ __forceinline__ uint2 lds64(uint32_t a) {
    uint2 v;
    asm volatile("ld.shared.v2.u32 {%0,%1}, [%2];" : "=r"(v.x), "=r"(v.y) : "r"(a));
    return v;
}
__device__ __forceinline__ uint32_t lds32(uint32_t a) {
    uint32_t v;
    asm volatile("ld.shared.u32 %0, [%1];" : "=r"(v) : "r"(a));
    return v;
}
__device__ __forceinline__ uint32_t ld_relaxed(const unsigned int* p) {
    uint32_t v;
    asm volatile("ld.relaxed.gpu.global.u32 %0, [%1];" : "=r"(v) : "l"(p) : "memory");
    return v;
}
__device__ __forceinline__ uint4 ld_relaxed4(const uint32_t* p) {
    uint4 v;
    asm volatile("ld.relaxed.gpu.global.v4.u32 {%0,%1,%2,%3}, [%4];" : "=r"(v.x), "=r"(v.y), "=r"(v.z), "=r"(v.w) : "l"(p) : "memory");
    return v;
}
__device__ __forceinline__ uint2 ld_relaxed2(const uint32_t* p) {
    uint2 v;
    asm volatile("ld.relaxed.gpu.global.v2.u32 {%0,%1}, [%2];" : "=r"(v.x), "=r"(v.y) : "l"(p) : "memory");
    return v;
}
__device__ __forceinline__ void st_relaxed4(uint32_t* p, uint32_t x, uint32_t y, uint32_t z, uint32_t w) {
    asm volatile("st.relaxed.gpu.global.v4.u32 [%0], {%1,%2,%3,%4};" ::"l"(p), "r"(x), "r"(y), "r"(z), "r"(w) : "memory");
}
__device__ __forceinline__ void red_add_if(bool p_, unsigned int* p, uint32_t n) {
    asm volatile("{\n.reg .pred P;\nsetp.ne.u32 P, %1, 0;\n@P red.relaxed.gpu.global.add.u32 [%0], %2;\n}" ::"l"(p), "r"((uint32_t)p_), "r"(n) : "memory");
}
__device__ __forceinline__ uint32_t pack_bf16(float lo, float hi) {
    uint32_t r;
    asm("cvt.rn.bf16x2.f32 %0, %1, %2;" : "=r"(r) : "f"(hi), "f"(lo));
    return r;
}
__device__ __forceinline__ uint32_t dequant2(int lo, int hi, uint32_t z, uint32_t s) {
    uint32_t x = pack_bf16(__int2float_rn(lo), __int2float_rn(hi));
    uint32_t r;
    asm("sub.rn.bf16x2 %0, %1, %2;" : "=r"(r) : "r"(x), "r"(z));
    asm("mul.rn.bf16x2 %0, %1, %2;" : "=r"(r) : "r"(r), "r"(s));
    return r;
}
__device__ __forceinline__ void mma_bf16(float (&c)[4], uint32_t a0, uint32_t a1, uint32_t a2, uint32_t a3, uint32_t b0,
                                         uint32_t b1) {
    asm("mma.sync.aligned.m16n8k16.row.col.f32.bf16.bf16.f32 {%0,%1,%2,%3}, {%4,%5,%6,%7}, {%8,%9}, {%0,%1,%2,%3};"
        : "+f"(c[0]), "+f"(c[1]), "+f"(c[2]), "+f"(c[3])
        : "r"(a0), "r"(a1), "r"(a2), "r"(a3), "r"(b0), "r"(b1));
}
__device__ __forceinline__ float ex2(float x) {
    float y;
    asm("ex2.approx.ftz.f32 %0, %1;" : "=f"(y) : "f"(x));
    return y;
}
__device__ __forceinline__ uint32_t tagged(uint32_t x, uint32_t tag) { return (x & ~1u) | tag; }
__device__ __forceinline__ uint32_t tagged(float x, uint32_t tag) { return tagged(__float_as_uint(x), tag); }
__device__ __forceinline__ uint32_t split_p(float a, float b, bool lo, uint32_t tag) {
    uint32_t h = tagged(pack_bf16(a, b), tag);
    if (lo) h = tagged(pack_bf16(a - __uint_as_float(h << 16), b - __uint_as_float(h & 0xffff0000u)), tag);
    return h;
}
__device__ __forceinline__ uint32_t split_p(float a, float b, bool lo) {
    uint32_t h = pack_bf16(a, b);
    if (lo) h = pack_bf16(a - __uint_as_float(h << 16), b - __uint_as_float(h & 0xffff0000u));
    return h;
}
__device__ __forceinline__ void st_relaxed2(uint32_t* p, uint32_t x, uint32_t y) {
    asm volatile("st.relaxed.gpu.global.v2.u32 [%0], {%1,%2};" ::"l"(p), "r"(x), "r"(y) : "memory");
}
__device__ __forceinline__ uint32_t bad4(uint4 v, uint32_t tag) { return ((v.x ^ tag) | (v.y ^ tag)) | ((v.z ^ tag) | (v.w ^ tag)); }
__device__ __forceinline__ uint32_t pin(uint32_t x) { return __shfl_sync(0xffffffffu, x, threadIdx.x & 31); }
template <typename T>
__device__ __forceinline__ T* pin(T* p) {
    const uint64_t a = reinterpret_cast<uint64_t>(p);
    return reinterpret_cast<T*>((uint64_t)pin((uint32_t)(a >> 32)) << 32 | pin((uint32_t)a));
}

__global__ void __launch_bounds__(kThreads, 1)
kivi_decode_kernel(const int* __restrict__ qk, const __nv_bfloat16* __restrict__ k_scales,
                   const __nv_bfloat16* __restrict__ k_zeros, const __nv_bfloat16* __restrict__ v_scales,
                   const __nv_bfloat16* __restrict__ v_zeros, const __nv_bfloat16* __restrict__ q,
                   __nv_bfloat16* __restrict__ out, uint32_t* __restrict__ xch, unsigned int* __restrict__ prog,
                   const __grid_constant__ CUtensorMap map_v, const __grid_constant__ CUtensorMap map_w) {
    extern __shared__ uint8_t smem_raw[];
    unsigned long long t0 = 0, t1 = 0, t2 = 0;
    TGET(t0);
    const int bh = blockIdx.x / kSplit, r = blockIdx.x % kSplit;
    const int unit0 = bh * kUnitsPerBH + r;
    const char* gk = reinterpret_cast<const char*>(qk);
    if (PF >= 1) asm volatile("prefetch.global.L2 [%0];" ::"l"(gk + (size_t)unit0 * kTile + threadIdx.x * 128) : "memory");
    if (PF >= 2) asm volatile("prefetch.global.L2 [%0];" ::"l"(gk + (size_t)unit0 * kTile + kTile - 128 - threadIdx.x * 128) : "memory");

    const uint32_t sb = (smem_u32(smem_raw) + 1023u) & ~1023u;
    const uint32_t bar_kfull = sb + kOffBar;
    const uint32_t bar_kempty = bar_kfull + kStages * 8;
    const uint32_t bar_vempty = bar_kempty + kStages * 8;
    const uint32_t bar_vfull = bar_vempty + kStages * 8;
    const uint32_t bar_sig = bar_vfull + kStages * 8;
    uint64_t pol;
    asm volatile("createpolicy.fractional.L2::evict_first.b64 %0, 1.0;" : "=l"(pol));
    if (threadIdx.x < 32) {
        if (elect_one()) {
            mbar_init(bar_kfull, 1);
            mbar_init(bar_kfull + 8, 1);
            asm volatile("fence.mbarrier_init.release.cluster;" ::: "memory");
            mbar_expect_tx(bar_kfull, kTile + 2 * kKsBytes + 2 * kVsBytes);
            bulk_load(sb + kOffK, gk + (size_t)unit0 * kTile, kTile, bar_kfull, pol);
            TGET(t1);
            if (K1TOP) {
                mbar_expect_tx(bar_kfull + 8, kTile + 2 * kKsBytes + 2 * kVsBytes);
                bulk_load(sb + kOffK + kTile, gk + (size_t)(unit0 + kSplit) * kTile, kTile, bar_kfull + 8, pol);
            }
        }
        __syncwarp();
    }
    const int warp = __shfl_sync(0xffffffffu, threadIdx.x >> 5, 0), lane = threadIdx.x & 31;

    if (warp == 0) {
        if (elect_one()) {
#pragma unroll
            for (int s = 0; s < kStages; s++) {
                if (s >= 2) mbar_init(bar_kfull + s * 8, 1);
                mbar_init(bar_kempty + s * 8, kCW);
                mbar_init(bar_vempty + s * 8, kCW);
                mbar_init(bar_vfull + s * 8, 1);
            }
            mbar_init(bar_sig, 1);
            mbar_init(bar_sig + 8, 1);
            mbar_init(bar_sig + 16, 1);
            asm volatile("fence.mbarrier_init.release.cluster;" ::: "memory");
            asm volatile("prefetch.tensormap [%0];" ::"l"(&map_v) : "memory");
        }
        __syncwarp();
        asm volatile("bar.arrive 0, %0;" ::"n"(kThreads) : "memory");
        if (elect_one()) {
            const char* gks = reinterpret_cast<const char*>(k_scales);
            const char* gkz = reinterpret_cast<const char*>(k_zeros);
            const char* gvs = reinterpret_cast<const char*>(v_scales);
            const char* gvz = reinterpret_cast<const char*>(v_zeros);
            const int stag = STAG == 0 ? 0 : STAG == 1 ? (int)(__brev(blockIdx.x) >> 25) - 64 : STAG == 2 ? (int)(__brev(bh) >> 25) - 64 : (int)(__brev(bh) >> 26) - 32;
            uint32_t seen = 0;
            bool pace = true;
            int st = 0, iv = 0, sk = 0, sv = 0;
            bool do_k = true;
            uint32_t phk = 1, phv = 1;
#pragma unroll 1
            for (int j = 0; j < 2 * kUnits; j++) {
                constexpr int d0 = (int)(D0 * kCtas), d1 = (int)(D1 * kCtas);
                const int dj = j <= J0 ? d0 : j >= J1 ? d1 : d0 + (d1 - d0) * (j - J0) / (J1 - J0);
                const int sj = (FADE && j > 127 - FADE) ? stag * (127 - j) / FADE : stag;
                const int need = (j + 1) * kCtas - dj + sj - (LSPLIT && j == 2 * kUnits - 1 ? LEARLY : 0) - (j == 127 ? E127 : j == 126 ? E126 : 0);
                int it = 0;
                while (pace && (int)seen < need) {
                    if (PSLEEP && it) __nanosleep(PSLEEP);
                    seen = ld_relaxed(prog) & (kProgTotal - 1);
                    if (++it > 128) pace = false;
                }
                if (j == JA) mbar_arrive(bar_sig);
                if (j == JB) mbar_arrive(bar_sig + 8);
                if (do_k) {
                    const bool extra = st >= SE && st < SE + kEnd;
                    const int ik = st < SE ? st : extra ? kMain + st - SE : st - kEnd;
                    const int u = unit0 + ik * kSplit;
                    const uint32_t bar = bar_kfull + sk * 8;
                    mbar_wait(bar_kempty + sk * 8, phk);
                    const uint32_t nvs = ik < kMain ? kVsBytes : ik == kMain ? kVsEndBytes : 0;
                    if (j >= 1 + K1TOP) {
                        mbar_expect_tx(bar, kTile + 2 * kKsBytes + 2 * nvs);
                        bulk_load(sb + kOffK + sk * kTile, gk + (size_t)u * kTile, kTile, bar, pol);
                    }
                    bulk_load(sb + kOffKs + sk * 2 * kKsBytes, gks + (size_t)u * kKsBytes, kKsBytes, bar, pol);
                    bulk_load(sb + kOffKs + sk * 2 * kKsBytes + kKsBytes, gkz + (size_t)u * kKsBytes, kKsBytes, bar, pol);
                    if (nvs) {
                        const uint32_t dst = ik < kMain ? sb + kOffVs + (ik & (kVsRing - 1)) * 2 * kVsBytes : sb + kOffVsEnd;
                        const size_t off = (size_t)(ik < kMain ? u : u - r) * kVsBytes;
                        bulk_load(dst, gvs + off, nvs, bar, pol);
                        bulk_load(dst + nvs, gvz + off, nvs, bar, pol);
                    }
                    do_k = extra || st == 0;
                    st++;
                    if (++sk == kStages) {
                        sk = 0;
                        phk ^= 1;
                    }
                } else if (iv >= kMain) {
                    const uint32_t bar = bar_kfull + sk * 8;
                    mbar_wait(bar_kempty + sk * 8, phk);
                    const bool last = LSPLIT && iv == kUnits - 1;
                    mbar_expect_tx(bar, last ? kTile / 2 : kTile);
                    tensor_load_5d(sb + kOffK + sk * kTile, &map_w, r * 16, 0, (unit0 - r + iv * kSplit) / 2, bar, pol);
                    if (last) {
                        __nanosleep(LSPLIT);
                        mbar_expect_tx(bar_sig + 16, kTile / 2);
                    }
                    tensor_load_5d(sb + kOffK + sk * kTile + kTile / 2, &map_w, r * 16, 16, (unit0 - r + iv * kSplit) / 2, last ? bar_sig + 16 : bar, pol);
                    iv++;
                    if (++sk == kStages) {
                        sk = 0;
                        phk ^= 1;
                    }
                } else {
                    const int u = unit0 + iv * kSplit;
                    const uint32_t bar = bar_vfull + sv * 8;
                    mbar_wait(bar_vempty + sv * 8, phv);
                    mbar_expect_tx(bar, kTile);
                    tensor_load_4d(sb + kOffV + sv * kTile, &map_v, 0, u * (kTok / 8), bar, pol);
                    iv++;
                    do_k = st < kUnits;
                    if (++sv == kStages) {
                        sv = 0;
                        phv ^= 1;
                    }
                }
                if (j == 4) TGET(t2);
                if (j == 16) {
                    const uint32_t tag = ((ld_relaxed(prog) / kProgTotal) & 1) ^ 1;
                    asm volatile("st.shared.u32 [%0], %1;" ::"r"(sb + kOffTag), "r"(tag) : "memory");
                }
                if (j == 100) asm volatile("prefetch.tensormap [%0];" ::"l"(&map_w) : "memory");
            }
            TPUT(0, t0); TPUT(1, t1); TPUT(2, t2);
        }
        __syncwarp();
        return;
    }

    const int g = lane >> 2, c = lane & 3;
    const int hsel = c >> 1;
    const int ohead = 2 * (c & 1) + hsel;
    const uint32_t* const xg = xch + (size_t)bh * kSplit * kXWords;
    if (warp == kCW + 1) {
        const uint32_t* xoin = pin(xg + kXo + ohead * kD + 16 * r + 2 * g);
        const uint32_t red_rd = pin(sb + kOffRed + lane * 16);
        uint32_t* const optr = pin(reinterpret_cast<uint32_t*>(out + (size_t)(bh * kRep + ohead) * kD + 16 * r + 2 * g));
        asm volatile("bar.sync 0, %0;" ::"n"(kThreads) : "memory");
        mbar_wait(bar_sig, 0);
        const uint32_t tag = lds32(sb + kOffTag);
        uint4 ml;
        int it = 0;
        uint2 o[kSplit];
        do {
            ml = ld_relaxed4(xg + g * kXWords + kXm + c * 4);
            if (++it > (1 << 22)) __trap();
        } while (__any_sync(0xffffffffu, bad4(ml, tag) & 1));
        TGET(t2);
        float wm[kSplit], we[kSplit];
        {
            const float m = __uint_as_float(ml.x);
            float M = fmaxf(m, __shfl_xor_sync(0xffffffffu, m, 4));
            M = fmaxf(M, __shfl_xor_sync(0xffffffffu, M, 8));
            M = fmaxf(M, __shfl_xor_sync(0xffffffffu, M, 16));
            const float w = ex2(m - M);
            float L = w * __uint_as_float(ml.y);
            L += __shfl_xor_sync(0xffffffffu, L, 4);
            L += __shfl_xor_sync(0xffffffffu, L, 8);
            L += __shfl_xor_sync(0xffffffffu, L, 16);
            const float inv = 1.f / L;
            const float w0 = w * inv, w1 = ex2(__uint_as_float(ml.z) - M) * inv;
#pragma unroll
            for (int k = 0; k < kSplit; k++) {
                wm[k] = __shfl_sync(0xffffffffu, w0, k * 4 + ohead);
                we[k] = __shfl_sync(0xffffffffu, w1, k * 4 + ohead);
            }
        }
        mbar_wait(bar_sig + 8, 0);
#pragma unroll
        for (int k = 0; k < kSplit; k++) o[k] = ld_relaxed2(xoin + k * kXWords);
        while (true) {
            uint32_t bad = 0;
#pragma unroll
            for (int k = 0; k < kSplit; k++) bad |= (((o[k].x ^ tag) | (o[k].y ^ tag)) & 1) << k;
            bad = __reduce_or_sync(0xffffffffu, bad);
            if (!bad) break;
#pragma unroll
            for (int k = 0; k < kSplit; k++)
                if (bad >> k & 1) o[k] = ld_relaxed2(xoin + k * kXWords);
            if (++it > (1 << 22)) __trap();
        }
        TGET(t1);
        float y0 = 0.f, y1 = 0.f;
#pragma unroll
        for (int k = 0; k < kSplit; k++) {
            y0 += wm[k] * __uint_as_float(o[k].x);
            y1 += wm[k] * __uint_as_float(o[k].y);
        }
        y0 = __uint_as_float(pin(__float_as_uint(y0)));
        y1 = __uint_as_float(pin(__float_as_uint(y1)));
        asm volatile("bar.sync 2, %0;" ::"n"(kCW * 32 + 32) : "memory");
        float u0 = 0.f, u1 = 0.f;
#pragma unroll
        for (int k = 0; k < kCW; k++) {
            const float4 z = lds128f(red_rd + k * 512);
            y0 += we[2 * k] * z.x;
            y1 += we[2 * k] * z.y;
            u0 += we[2 * k + 1] * z.z;
            u1 += we[2 * k + 1] * z.w;
        }
        *optr = pack_bf16(y0 + u0, y1 + u1);
        if (lane == 0) { TSTAMP(11); TPUT(13, t2); TPUT(14, t1); }
        return;
    }

    const int cw = warp - 1;
    const int par = g & 1;
    uint2 qf[4][2];
    {
        const __nv_bfloat16* qrow = q + (size_t)(bh * kRep + (g & 3)) * kD + 4 * c;
#pragma unroll
        for (int P = 0; P < 4; P++) {
            qf[P][0] = __ldg(reinterpret_cast<const uint2*>(qrow + 32 * P));
            qf[P][1] = __ldg(reinterpret_cast<const uint2*>(qrow + 32 * P + 16));
        }
    }
    const uint32_t k_lane0 = sb + kOffK + (16 * cw + g) * 512 + c * 16 + par * 64;
    const uint32_t ks_lane0 = sb + kOffKs + (cw >> 1) * (kD * 2) + c * 8 + par * 32;
    const uint32_t v_lane0 = sb + kOffV + cw * 1024 + (2 * c) * 128 + ((g ^ (2 * c)) * 16);
    const uint32_t vs_lane = sb + kOffVs + (2 * c) * 2;
    const uint32_t sc_rd = sb + kOffSc + ((g & 3) * 4 + c) * 16;
    const uint32_t sc_wr = sc_rd + cw * 256;
    uint32_t* const xme = xch + (size_t)blockIdx.x * kXWords;
    uint32_t* const xo = xme + kXo + ohead * kD + 32 * cw + 4 * g;
    const bool reporter = threadIdx.x == 32;

    const float sl2e = 0.08838834764831845f * 1.4426950408889634f;
    float acc[2][4];
#pragma unroll
    for (int m = 0; m < 2; m++)
#pragma unroll
        for (int e = 0; e < 4; e++) acc[m][e] = 0.f;
    float m_run = -FLT_MAX, l_run = 0.f, a0 = 1.f, a1 = 1.f, m_pub = 0.f;
    uint4 pf[kEnd][2][2];
    const int gather_at = SG + (blockIdx.x & 31);
    uint32_t tag = 0;

    asm volatile("bar.sync 0, %0;" ::"n"(kThreads) : "memory");
    int sk = 0, sv = 0, iv = 0;
    uint32_t phk = 0, phv = 0;
    uint32_t pb[4][2], pn[4][2];
#pragma unroll
    for (int k = 0; k < 4; k++) pb[k][0] = pb[k][1] = 0;
#pragma unroll 1
    for (int i = 0; i <= kUnits; i++) {
      if (i < kUnits) {
        mbar_wait(bar_kfull + sk * 8, phk);
        if (reporter && i == 0) TSTAMP(3);
        if (reporter && i == kUnits - 1) TSTAMP(4);
        float sa[2][2][4];
#pragma unroll
        for (int u = 0; u < 2; u++)
#pragma unroll
            for (int e = 0; e < 2; e++)
#pragma unroll
                for (int k = 0; k < 4; k++) sa[u][e][k] = 0.f;
#pragma unroll
        for (int P = 0; P < 4; P++)
#pragma unroll
            for (int e = 0; e < 2; e++) {
                const uint32_t ka = (k_lane0 ^ (e * 64)) + sk * kTile + P * 128;
                const uint32_t sa_ = (ks_lane0 ^ (e * 32)) + sk * (2 * kKsBytes) + P * 64;
                const uint2 zr = lds64(sa_ + kKsBytes);
                const uint2 sc = lds64(sa_);
#pragma unroll
                for (int u = 0; u < 2; u++) {
                    const int4 x = lds128(ka + u * 8 * 512);
                    mma_bf16(sa[u][e], qf[P][e].x, qf[P][e ^ 1].x, qf[P][e].y, qf[P][e ^ 1].y,
                             dequant2(x.x, x.y, zr.x, sc.x), dequant2(x.z, x.w, zr.y, sc.y));
                }
            }
        __syncwarp();
        if (lane == 0) mbar_arrive(bar_kempty + sk * 8);
        red_add_if(reporter, prog, 1);
        if (g < 4)
            sts128f(sc_wr + (i & 3) * 1024, (sa[0][0][0] + sa[0][1][0]) * sl2e, (sa[0][0][3] + sa[0][1][3]) * sl2e,
                    (sa[1][0][0] + sa[1][1][0]) * sl2e, (sa[1][0][3] + sa[1][1][3]) * sl2e);
        if (++sk == kStages) {
            sk = 0;
            phk ^= 1;
        }
        asm volatile("bar.sync 1, %0;" ::"n"(kCW * 32) : "memory");
        float4 t[4];
#pragma unroll
        for (int kk = 0; kk < 4; kk++) t[kk] = lds128f(sc_rd + (i & 3) * 1024 + kk * 256);
        float mx = m_run;
#pragma unroll
        for (int kk = 0; kk < 4; kk++) mx = fmaxf(mx, fmaxf(fmaxf(t[kk].x, t[kk].y), fmaxf(t[kk].z, t[kk].w)));
        mx = fmaxf(mx, __shfl_xor_sync(0xffffffffu, mx, 1));
        mx = fmaxf(mx, __shfl_xor_sync(0xffffffffu, mx, 2));
        const float alpha = ex2(m_run - mx);
        m_run = mx;
        a0 *= __shfl_sync(0xffffffffu, alpha, ((2 * c) & 3) * 4);
        a1 *= __shfl_sync(0xffffffffu, alpha, ((2 * c + 1) & 3) * 4);
        float ls = 0.f;
#pragma unroll
        for (int kk = 0; kk < 4; kk++) {
            const float p0 = ex2(t[kk].x - mx), p1 = ex2(t[kk].y - mx), p2 = ex2(t[kk].z - mx), p3 = ex2(t[kk].w - mx);
            ls += (p0 + p1) + (p2 + p3);
            pn[kk][0] = split_p(p0, p1, g >= 4);
            pn[kk][1] = split_p(p2, p3, g >= 4);
        }
        l_run = l_run * alpha + ls;
        if (i >= SE && i < SE + kEnd) {
            if (i == SE + kEnd - 1) {
                tag = lds32(sb + kOffTag);
                m_pub = mx;
                if (cw < kEnd) {
                    uint32_t w[8];
#pragma unroll
                    for (int kk = 0; kk < 4; kk++) {
                        const float4 u = lds128f(sc_rd + ((SE + cw) & 3) * 1024 + kk * 256);
                        w[2 * kk] = split_p(ex2(u.x - mx), ex2(u.y - mx), g >= 4, tag);
                        w[2 * kk + 1] = split_p(ex2(u.z - mx), ex2(u.w - mx), g >= 4, tag);
                    }
                    st_relaxed4(xme + kXp + cw * 256 + lane * 4, w[0], w[1], w[2], w[3]);
                    st_relaxed4(xme + kXp + cw * 256 + lane * 4 + 128, w[4], w[5], w[6], w[7]);
                }
            }
            continue;
        }
        if (i == gather_at) {
            int it = 0;
            uint32_t bad;
            do {
                bad = 0;
#pragma unroll
                for (int e = 0; e < kEnd; e++)
#pragma unroll
                    for (int s = 0; s < 2; s++)
#pragma unroll
                        for (int h = 0; h < 2; h++) pf[e][s][h] = ld_relaxed4(xg + (2 * cw + s) * kXWords + kXp + e * 256 + lane * 4 + h * 128);
#pragma unroll
                for (int e = 0; e < kEnd; e++)
#pragma unroll
                    for (int s = 0; s < 2; s++)
#pragma unroll
                        for (int h = 0; h < 2; h++) bad |= bad4(pf[e][s][h], tag);
                if (++it > (1 << 22)) __trap();
            } while (__any_sync(0xffffffffu, bad & 1));
        }
        if (i == INIT_AT) {
            const uint32_t nt = tag ^ 1;
            st_relaxed4(xo, nt, nt, nt, nt);
            if (cw == 3 && c == 0 && g < 4) st_relaxed4(xme + kXm + g * 4, nt, nt, nt, nt);
        }
        if (i == kUnits - 1 && cw == 3) {
            float l = l_run + __shfl_xor_sync(0xffffffffu, l_run, 1);
            l += __shfl_xor_sync(0xffffffffu, l, 2);
            if (c == 0 && g < 4) st_relaxed4(xme + kXm + g * 4, tagged(m_run, tag), tagged(l, tag), tagged(m_pub, tag), tag);
        }
      }
        if (i > 0) {
            const uint32_t va0 = v_lane0 + sv * kTile, va1 = va0 ^ (128 + 16);
            const uint32_t vsb = vs_lane + (iv & (kVsRing - 1)) * (2 * kVsBytes);
            iv++;
            uint32_t vs[4][2], vz[4][2];
#pragma unroll
            for (int kk = 0; kk < 4; kk++)
#pragma unroll
                for (int u = 0; u < 2; u++) {
                    vs[kk][u] = lds32(vsb + kk * 32 + u * 16);
                    vz[kk][u] = lds32(vsb + kVsBytes + kk * 32 + u * 16);
                }
            mbar_wait(bar_vfull + sv * 8, phv);
#pragma unroll
            for (int kk = 0; kk < 4; kk++) {
                const int4 x0 = lds128(va0 + kk * 8192);
                const int4 x1 = lds128(va1 + kk * 8192);
                const int4 x2 = lds128(va0 + kk * 8192 + 4096);
                const int4 x3 = lds128(va1 + kk * 8192 + 4096);
                mma_bf16(acc[0], dequant2(x0.x, x1.x, vz[kk][0], vs[kk][0]), dequant2(x0.y, x1.y, vz[kk][0], vs[kk][0]),
                         dequant2(x2.x, x3.x, vz[kk][1], vs[kk][1]), dequant2(x2.y, x3.y, vz[kk][1], vs[kk][1]), pb[kk][0], pb[kk][1]);
                mma_bf16(acc[1], dequant2(x0.z, x1.z, vz[kk][0], vs[kk][0]), dequant2(x0.w, x1.w, vz[kk][0], vs[kk][0]),
                         dequant2(x2.z, x3.z, vz[kk][1], vs[kk][1]), dequant2(x2.w, x3.w, vz[kk][1], vs[kk][1]), pb[kk][0], pb[kk][1]);
            }
            __syncwarp();
            if (lane == 0) mbar_arrive(bar_vempty + sv * 8);
            red_add_if(reporter, prog, 1);
            if (++sv == kStages) {
                sv = 0;
                phv ^= 1;
            }
        }
#pragma unroll
        for (int m = 0; m < 2; m++) {
            acc[m][0] *= a0;
            acc[m][1] *= a1;
            acc[m][2] *= a0;
            acc[m][3] *= a1;
        }
        a0 = a1 = 1.f;
#pragma unroll
        for (int kk = 0; kk < 4; kk++) {
            pb[kk][0] = pn[kk][0];
            pb[kk][1] = pn[kk][1];
        }
    }
    {
        float o[4];
#pragma unroll
        for (int m = 0; m < 2; m++)
#pragma unroll
            for (int e = 0; e < 2; e++) {
                const float keep = hsel ? acc[m][2 * e + 1] : acc[m][2 * e];
                const float send = hsel ? acc[m][2 * e] : acc[m][2 * e + 1];
                o[2 * m + e] = keep + __shfl_xor_sync(0xffffffffu, send, 2);
            }
        st_relaxed4(xo, tagged(o[0], tag), tagged(o[1], tag), tagged(o[2], tag), tagged(o[3], tag));
    }
    if (reporter) TSTAMP(6);

    const uint32_t w_lane = pin(sb + kOffK + cw * 4096 + ((c & 1) + 4 * hsel) * 64 + (((g >> 1) ^ (2 * hsel)) * 16) + (g & 1) * 8);
    const uint32_t red_wr = pin(sb + kOffRed + cw * 512 + lane * 16);
    float a[2][4];
#pragma unroll
    for (int s = 0; s < 2; s++)
#pragma unroll
        for (int k = 0; k < 4; k++) a[s][k] = 0.f;
#pragma unroll 1
    for (int e = 0; e < kEnd; e++) {
        const uint32_t wa0 = w_lane + sk * kTile, wa1 = wa0 ^ (128 + 16);
        const uint32_t vsb = sb + kOffVsEnd + (e * kSplit * kTok + cw * 2 * kTok + 2 * c) * 2;
        uint32_t vs[8][2], vz[8][2];
#pragma unroll
        for (int kk = 0; kk < 8; kk++)
#pragma unroll
            for (int u = 0; u < 2; u++) {
                vs[kk][u] = lds32(vsb + kk * 32 + u * 16);
                vz[kk][u] = lds32(vsb + kVsEndBytes + kk * 32 + u * 16);
            }
        t2 = t1;
        if (SPIN) mbar_spin(bar_kfull + sk * 8, phk);
        else mbar_wait(bar_kfull + sk * 8, phk);
        TGET(t1);
#pragma unroll
        for (int n = 0; n < 8; n++) {
            const int s = LSPLIT ? n >> 2 : n & 1, kk = LSPLIT ? n & 3 : n >> 1;
            if (LSPLIT && n == 4 && e == kEnd - 1) { mbar_wait(bar_sig + 16, 0); TGET(t1); }
            const int k8 = s * 4 + kk;
            const uint2 x0 = lds64(wa0 + s * 16384 + kk * 1024);
            const uint2 x1 = lds64(wa1 + s * 16384 + kk * 1024);
            const uint2 x2 = lds64(wa0 + s * 16384 + kk * 1024 + 512);
            const uint2 x3 = lds64(wa1 + s * 16384 + kk * 1024 + 512);
            const uint4 p = pf[0][s][kk >> 1];
            mma_bf16(a[s], dequant2(x0.x, x1.x, vz[k8][0], vs[k8][0]), dequant2(x0.y, x1.y, vz[k8][0], vs[k8][0]),
                     dequant2(x2.x, x3.x, vz[k8][1], vs[k8][1]), dequant2(x2.y, x3.y, vz[k8][1], vs[k8][1]),
                     (kk & 1) ? p.z : p.x, (kk & 1) ? p.w : p.y);
        }
        if (e == kEnd - 1) break;
        red_add_if(reporter, prog, 1);
#pragma unroll
        for (int n = 0; n + 1 < kEnd; n++)
#pragma unroll
            for (int s = 0; s < 2; s++)
#pragma unroll
                for (int h = 0; h < 2; h++) pf[n][s][h] = pf[n + 1][s][h];
        if (++sk == kStages) {
            sk = 0;
            phk ^= 1;
        }
    }
    float y[4];
#pragma unroll
    for (int s = 0; s < 2; s++)
#pragma unroll
        for (int e = 0; e < 2; e++)
            y[2 * s + e] = (hsel ? a[s][2 * e + 1] : a[s][2 * e]) + __shfl_xor_sync(0xffffffffu, hsel ? a[s][2 * e] : a[s][2 * e + 1], 2);
    sts128f(red_wr, y[0], y[1], y[2], y[3]);
    asm volatile("bar.arrive 2, %0;" ::"n"(kCW * 32 + 32) : "memory");
    red_add_if(reporter, prog, 1);
}

typedef CUresult (*EncodeTiledFn)(CUtensorMap*, CUtensorMapDataType, cuuint32_t, void*, const cuuint64_t*,
                                  const cuuint64_t*, const cuuint32_t*, const cuuint32_t*, CUtensorMapInterleave,
                                  CUtensorMapSwizzle, CUtensorMapL2promotion, CUtensorMapFloatOOBfill);

}

extern "C" void kernel_launch(void* const* d_in, const int* in_sizes, int n_in, void* d_out, int out_size) {
    (void)in_sizes;
    (void)n_in;
    (void)out_size;
    static EncodeTiledFn encode = nullptr;
    static uint32_t* scratch = nullptr;
    if (!encode) {
        cudaGetSymbolAddress((void**)&scratch, g_scratch);
        cudaDriverEntryPointQueryResult qr;
        void* fn = nullptr;
        cudaGetDriverEntryPoint("cuTensorMapEncodeTiled", &fn, cudaEnableDefault, &qr);
        encode = (EncodeTiledFn)fn;
        cudaFuncSetAttribute(kivi_decode_kernel, cudaFuncAttributeMaxDynamicSharedMemorySize, kSmemBytes);
    }
    CUtensorMap map_v, map_w;
    const cuuint32_t estr[5] = {1, 1, 1, 1, 1};
    {
        const cuuint64_t gdim[4] = {32, 8, 4, (cuuint64_t)kBH * kS / 8};
        const cuuint64_t gstr[3] = {512, 128, 4096};
        const cuuint32_t box[4] = {32, 8, 4, kTok / 8};
        encode(&map_v, CU_TENSOR_MAP_DATA_TYPE_INT32, 4, d_in[2], gdim, gstr, box, estr, CU_TENSOR_MAP_INTERLEAVE_NONE,
               CU_TENSOR_MAP_SWIZZLE_128B, CU_TENSOR_MAP_L2_PROMOTION_NONE, CU_TENSOR_MAP_FLOAT_OOB_FILL_NONE);
    }
    {
        const cuuint64_t gdim[5] = {kD, 2, 2, 32, (cuuint64_t)kBH * kS / 128};
        const cuuint64_t gstr[4] = {1024, 512, 2048, 65536};
        const cuuint32_t box[5] = {16, 2, 2, 16, 4};
        encode(&map_w, CU_TENSOR_MAP_DATA_TYPE_INT32, 5, d_in[2], gdim, gstr, box, estr, CU_TENSOR_MAP_INTERLEAVE_NONE,
               CU_TENSOR_MAP_SWIZZLE_64B, (CUtensorMapL2promotion)PROMO, CU_TENSOR_MAP_FLOAT_OOB_FILL_NONE);
    }
    kivi_decode_kernel<<<kCtas, kThreads, kSmemBytes>>>(
        (const int*)d_in[1], (const __nv_bfloat16*)d_in[3], (const __nv_bfloat16*)d_in[4], (const __nv_bfloat16*)d_in[5],
        (const __nv_bfloat16*)d_in[6], (const __nv_bfloat16*)d_in[0], (__nv_bfloat16*)d_out, scratch,
        scratch + kCtas * kXWords, map_v, map_w);
}
```

```cpp
#include <cuda_runtime.h>
#include <cuda_bf16.h>
#include <cuda.h>
#include <stdint.h>
#include <float.h>

namespace {

constexpr int kB = 2, kHq = 32, kHkv = 8, kS = 32768, kD = 128, kG = 32;
constexpr int kRep = kHq / kHkv;
constexpr int kBH = kB * kHkv;
constexpr int kSplit = 8;
constexpr int kCtas = kBH * kSplit;
constexpr int kTok = 64;
constexpr int kUnitsPerBH = kS / kTok;
constexpr int kUnits = kUnitsPerBH / kSplit;
constexpr int kEnd = 3;
constexpr int kMain = kUnits - kEnd;
constexpr int kOps = 2 * kUnits;
constexpr int kStages = 3;
constexpr int kVsRing = 8;
constexpr int kTile = kTok * kD * 4;
constexpr int kKsBytes = (kTok / kG) * kD * 2;
constexpr int kVsBytes = kTok * 2;
constexpr int kVsEndBytes = kEnd * kSplit * kVsBytes;
constexpr int kCW = 4;
constexpr int kThreads = (2 + kCW) * 32;

constexpr int kStepEndK = 14;
constexpr int kStepGather = 22;
constexpr int kOpTag = 16;
constexpr int kOpFetchMl = kOps - 2;
constexpr int kOpFetchO = kOps - 1;
constexpr int kDepth0 = 7 * kCtas, kDepth1 = 3 * kCtas, kRamp0 = 8, kRamp1 = 24;
constexpr uint32_t kProgTotal = kCtas * kOps;
static_assert((kProgTotal & (kProgTotal - 1)) == 0, "progress counter must wrap per launch");
static_assert(kEnd <= kStages && kEnd < kCW && 2 * kStepEndK > kOpTag + 2, "schedule");

constexpr int kXo = 0, kXp = kRep * kD, kXm = kXp + kEnd * 256, kXWords = kXm + 32;

constexpr int kOffK = 0;
constexpr int kOffV = kOffK + kStages * kTile;
constexpr int kOffKs = kOffV + kStages * kTile;
constexpr int kOffVs = kOffKs + kStages * 2 * kKsBytes;
constexpr int kOffVsEnd = kOffVs + kVsRing * 2 * kVsBytes;
constexpr int kOffSc = kOffVsEnd + 2 * kVsEndBytes;
constexpr int kOffRed = kOffSc + 4 * 1024;
constexpr int kOffBar = kOffRed + kCW * 512;
constexpr int kOffTag = kOffBar + (4 * kStages + 2) * 8;
constexpr int kSmemBytes = kOffTag + 16 + 1024;

__device__ __align__(128) uint32_t g_scratch[kCtas * kXWords + 32];

__device__ __forceinline__ uint32_t smem_u32(const void* p) { return (uint32_t)__cvta_generic_to_shared(p); }
__device__ __forceinline__ bool elect_one() {
    uint32_t p;
    asm volatile("{\n.reg .pred P;\nelect.sync _|P, 0xffffffff;\nselp.u32 %0, 1, 0, P;\n}" : "=r"(p));
    return p != 0;
}
__device__ __forceinline__ void mbar_init(uint32_t bar, uint32_t cnt) {
    asm volatile("mbarrier.init.shared::cta.b64 [%0], %1;" ::"r"(bar), "r"(cnt) : "memory");
}
__device__ __forceinline__ void mbar_expect_tx(uint32_t bar, uint32_t bytes) {
    asm volatile("mbarrier.arrive.expect_tx.shared::cta.b64 _, [%0], %1;" ::"r"(bar), "r"(bytes) : "memory");
}
__device__ __forceinline__ void mbar_arrive(uint32_t bar) {
    asm volatile("mbarrier.arrive.shared::cta.b64 _, [%0];" ::"r"(bar) : "memory");
}
__device__ __forceinline__ void mbar_wait(uint32_t bar, uint32_t parity) {
    uint32_t done;
    int it = 0;
    do {
        asm volatile(
            "{\n.reg .pred p;\nmbarrier.try_wait.parity.shared::cta.b64 p, [%1], %2;\nselp.u32 %0, 1, 0, p;\n}"
            : "=r"(done)
            : "r"(bar), "r"(parity)
            : "memory");
        if (++it > (1 << 24)) __trap();
    } while (!done);
}
__device__ __forceinline__ void bulk_load(uint32_t dst, const void* src, uint32_t bytes, uint32_t bar, uint64_t pol) {
    asm volatile(
        "cp.async.bulk.shared::cluster.global.mbarrier::complete_tx::bytes.L2::cache_hint [%0], [%1], %2, [%3], %4;" ::"r"(dst),
        "l"(src), "r"(bytes), "r"(bar), "l"(pol)
        : "memory");
}
__device__ __forceinline__ void tensor_load_4d(uint32_t dst, const CUtensorMap* m, int c0, int c3, uint32_t bar, uint64_t pol) {
    asm volatile(
        "cp.async.bulk.tensor.4d.shared::cluster.global.mbarrier::complete_tx::bytes.L2::cache_hint "
        "[%0], [%1, {%3, %4, %4, %5}], [%2], %6;" ::"r"(dst),
        "l"(m), "r"(bar), "r"(c0), "r"(0), "r"(c3), "l"(pol)
        : "memory");
}
__device__ __forceinline__ int4 lds128(uint32_t a) {
    int4 v;
    asm volatile("ld.shared.v4.s32 {%0,%1,%2,%3}, [%4];" : "=r"(v.x), "=r"(v.y), "=r"(v.z), "=r"(v.w) : "r"(a));
    return v;
}
__device__ __forceinline__ float4 lds128f(uint32_t a) {
    float4 v;
    asm volatile("ld.shared.v4.f32 {%0,%1,%2,%3}, [%4];" : "=f"(v.x), "=f"(v.y), "=f"(v.z), "=f"(v.w) : "r"(a));
    return v;
}
__device__ __forceinline__ uint2 lds64(uint32_t a) {
    uint2 v;
    asm volatile("ld.shared.v2.u32 {%0,%1}, [%2];" : "=r"(v.x), "=r"(v.y) : "r"(a));
    return v;
}
__device__ __forceinline__ uint32_t lds32(uint32_t a) {
    uint32_t v;
    asm volatile("ld.shared.u32 %0, [%1];" : "=r"(v) : "r"(a));
    return v;
}
__device__ __forceinline__ void sts128f(uint32_t a, float x, float y, float z, float w) {
    asm volatile("st.shared.v4.f32 [%0], {%1,%2,%3,%4};" ::"r"(a), "f"(x), "f"(y), "f"(z), "f"(w) : "memory");
}
__device__ __forceinline__ uint32_t ld_relaxed(const uint32_t* p) {
    uint32_t v;
    asm volatile("ld.relaxed.gpu.global.u32 %0, [%1];" : "=r"(v) : "l"(p) : "memory");
    return v;
}
__device__ __forceinline__ uint2 ld_relaxed2(const uint32_t* p) {
    uint2 v;
    asm volatile("ld.relaxed.gpu.global.v2.u32 {%0,%1}, [%2];" : "=r"(v.x), "=r"(v.y) : "l"(p) : "memory");
    return v;
}
__device__ __forceinline__ uint4 ld_relaxed4(const uint32_t* p) {
    uint4 v;
    asm volatile("ld.relaxed.gpu.global.v4.u32 {%0,%1,%2,%3}, [%4];" : "=r"(v.x), "=r"(v.y), "=r"(v.z), "=r"(v.w) : "l"(p) : "memory");
    return v;
}
__device__ __forceinline__ void st_relaxed4(uint32_t* p, uint32_t x, uint32_t y, uint32_t z, uint32_t w) {
    asm volatile("st.relaxed.gpu.global.v4.u32 [%0], {%1,%2,%3,%4};" ::"l"(p), "r"(x), "r"(y), "r"(z), "r"(w) : "memory");
}
__device__ __forceinline__ void red_inc(uint32_t* p) {
    asm volatile("red.relaxed.gpu.global.add.u32 [%0], 1;" ::"l"(p) : "memory");
}
__device__ __forceinline__ uint32_t pack_bf16(float lo, float hi) {
    uint32_t r;
    asm("cvt.rn.bf16x2.f32 %0, %1, %2;" : "=r"(r) : "f"(hi), "f"(lo));
    return r;
}
__device__ __forceinline__ float bf16_lo(uint32_t x) { return __uint_as_float(x << 16); }
__device__ __forceinline__ float bf16_hi(uint32_t x) { return __uint_as_float(x & 0xffff0000u); }
__device__ __forceinline__ uint32_t dequant2(int lo, int hi, uint32_t z, uint32_t s) {
    uint32_t x = pack_bf16(__int2float_rn(lo), __int2float_rn(hi));
    uint32_t r;
    asm("sub.rn.bf16x2 %0, %1, %2;" : "=r"(r) : "r"(x), "r"(z));
    asm("mul.rn.bf16x2 %0, %1, %2;" : "=r"(r) : "r"(r), "r"(s));
    return r;
}
__device__ __forceinline__ float2 logits2(float a, float b) {
    const float scale = 0.08838834764831845f, log2e = 1.4426950408889634f;
    uint32_t x = pack_bf16(a, b);
    x = pack_bf16(bf16_lo(x) * scale, bf16_hi(x) * scale);
    return make_float2(bf16_lo(x) * log2e, bf16_hi(x) * log2e);
}
__device__ __forceinline__ void mma_bf16(float (&c)[4], uint32_t a0, uint32_t a1, uint32_t a2, uint32_t a3, uint32_t b0,
                                         uint32_t b1) {
    asm("mma.sync.aligned.m16n8k16.row.col.f32.bf16.bf16.f32 {%0,%1,%2,%3}, {%4,%5,%6,%7}, {%8,%9}, {%0,%1,%2,%3};"
        : "+f"(c[0]), "+f"(c[1]), "+f"(c[2]), "+f"(c[3])
        : "r"(a0), "r"(a1), "r"(a2), "r"(a3), "r"(b0), "r"(b1));
}
__device__ __forceinline__ float ex2(float x) {
    float y;
    asm("ex2.approx.ftz.f32 %0, %1;" : "=f"(y) : "f"(x));
    return y;
}
__device__ __forceinline__ uint32_t split_p(float a, float b, bool lo) {
    uint32_t h = pack_bf16(a, b);
    if (lo) h = pack_bf16(a - bf16_lo(h), b - bf16_hi(h));
    return h;
}
__device__ __forceinline__ uint32_t tagged(uint32_t x, uint32_t tag) { return (x & ~1u) | tag; }
__device__ __forceinline__ uint32_t tagged(float x, uint32_t tag) { return tagged(__float_as_uint(x), tag); }
__device__ __forceinline__ uint32_t split_p_tagged(float a, float b, bool lo, uint32_t tag) {
    uint32_t h = tagged(pack_bf16(a, b), tag);
    if (lo) h = tagged(pack_bf16(a - bf16_lo(h), b - bf16_hi(h)), tag);
    return h;
}
__device__ __forceinline__ uint32_t stale(uint4 v, uint32_t tag) {
    return (((v.x ^ tag) | (v.y ^ tag)) | ((v.z ^ tag) | (v.w ^ tag))) & 1;
}
__device__ __forceinline__ uint32_t pin(uint32_t x) { return __shfl_sync(0xffffffffu, x, threadIdx.x & 31); }
__device__ __forceinline__ float pin(float x) { return __shfl_sync(0xffffffffu, x, threadIdx.x & 31); }
template <typename T>
__device__ __forceinline__ T* pin(T* p) {
    const uint64_t a = reinterpret_cast<uint64_t>(p);
    return reinterpret_cast<T*>((uint64_t)pin((uint32_t)(a >> 32)) << 32 | pin((uint32_t)a));
}
__device__ __forceinline__ void advance(int& s, uint32_t& ph) {
    if (++s == kStages) {
        s = 0;
        ph ^= 1;
    }
}

__global__ void __launch_bounds__(kThreads, 1)
kivi_decode_kernel(const int* __restrict__ qk, const __nv_bfloat16* __restrict__ k_scales,
                   const __nv_bfloat16* __restrict__ k_zeros, const __nv_bfloat16* __restrict__ v_scales,
                   const __nv_bfloat16* __restrict__ v_zeros, const __nv_bfloat16* __restrict__ q,
                   __nv_bfloat16* __restrict__ out, uint32_t* xch, uint32_t* prog,
                   const __grid_constant__ CUtensorMap map_v, const __grid_constant__ CUtensorMap map_w) {
    extern __shared__ uint8_t smem_raw[];
    const int bh = blockIdx.x / kSplit, r = blockIdx.x % kSplit;
    const int unit0 = bh * kUnitsPerBH + r;
    const char* gk = reinterpret_cast<const char*>(qk);
    asm volatile("prefetch.global.L2 [%0];" ::"l"(gk + (size_t)unit0 * kTile + threadIdx.x * 128) : "memory");

    const uint32_t sb = (smem_u32(smem_raw) + 1023u) & ~1023u;
    const uint32_t bar_kfull = sb + kOffBar;
    const uint32_t bar_kempty = bar_kfull + kStages * 8;
    const uint32_t bar_vempty = bar_kempty + kStages * 8;
    const uint32_t bar_vfull = bar_vempty + kStages * 8;
    const uint32_t bar_sig = bar_vfull + kStages * 8;
    uint64_t pol;
    asm volatile("createpolicy.fractional.L2::evict_first.b64 %0, 1.0;" : "=l"(pol));
    if (threadIdx.x < 32) {
        if (elect_one()) {
            mbar_init(bar_kfull, 1);
            asm volatile("fence.mbarrier_init.release.cluster;" ::: "memory");
            mbar_expect_tx(bar_kfull, kTile + 2 * kKsBytes + 2 * kVsBytes);
            bulk_load(sb + kOffK, gk + (size_t)unit0 * kTile, kTile, bar_kfull, pol);
        }
        __syncwarp();
    }
    const int warp = __shfl_sync(0xffffffffu, threadIdx.x >> 5, 0), lane = threadIdx.x & 31;

    if (warp == 0) {
        if (elect_one()) {
#pragma unroll
            for (int s = 0; s < kStages; s++) {
                if (s) mbar_init(bar_kfull + s * 8, 1);
                mbar_init(bar_kempty + s * 8, kCW);
                mbar_init(bar_vempty + s * 8, kCW);
                mbar_init(bar_vfull + s * 8, 1);
            }
            mbar_init(bar_sig, 1);
            mbar_init(bar_sig + 8, 1);
            asm volatile("fence.mbarrier_init.release.cluster;" ::: "memory");
            asm volatile("prefetch.tensormap [%0];" ::"l"(&map_v) : "memory");
        }
        __syncwarp();
        asm volatile("bar.arrive 0, %0;" ::"n"(kThreads) : "memory");
        if (elect_one()) {
            const char* gks = reinterpret_cast<const char*>(k_scales);
            const char* gkz = reinterpret_cast<const char*>(k_zeros);
            const char* gvs = reinterpret_cast<const char*>(v_scales);
            const char* gvz = reinterpret_cast<const char*>(v_zeros);
            const int stagger = (int)(__brev(bh) >> 26) - 32;
            uint32_t seen = 0;
            bool pace = true, do_k = true;
            int st = 0, iv = 0, sk = 0, sv = 0;
            uint32_t phk = 1, phv = 1;
#pragma unroll 1
            for (int j = 0; j < kOps; j++) {
                const int depth = j <= kRamp0   ? kDepth0
                                  : j >= kRamp1 ? kDepth1
                                                : kDepth0 + (kDepth1 - kDepth0) / (kRamp1 - kRamp0) * (j - kRamp0);
                const int need = (j + 1) * kCtas - depth + stagger;
                int it = 0;
                while (pace && (int)seen < need) {
                    seen = ld_relaxed(prog) & (kProgTotal - 1);
                    if (++it > 128) pace = false;
                }
                if (j == kOpFetchMl) mbar_arrive(bar_sig);
                if (j == kOpFetchO) mbar_arrive(bar_sig + 8);
                if (do_k) {
                    const bool extra = st >= kStepEndK && st < kStepEndK + kEnd;
                    const int ik = st < kStepEndK ? st : extra ? kMain + st - kStepEndK : st - kEnd;
                    const int u = unit0 + ik * kSplit;
                    const uint32_t bar = bar_kfull + sk * 8;
                    const uint32_t nvs = ik < kMain ? kVsBytes : ik == kMain ? kVsEndBytes : 0;
                    mbar_wait(bar_kempty + sk * 8, phk);
                    if (j) {
                        mbar_expect_tx(bar, kTile + 2 * kKsBytes + 2 * nvs);
                        bulk_load(sb + kOffK + sk * kTile, gk + (size_t)u * kTile, kTile, bar, pol);
                    }
                    bulk_load(sb + kOffKs + sk * 2 * kKsBytes, gks + (size_t)u * kKsBytes, kKsBytes, bar, pol);
                    bulk_load(sb + kOffKs + sk * 2 * kKsBytes + kKsBytes, gkz + (size_t)u * kKsBytes, kKsBytes, bar, pol);
                    if (nvs) {
                        const uint32_t dst = ik < kMain ? sb + kOffVs + (ik & (kVsRing - 1)) * 2 * kVsBytes : sb + kOffVsEnd;
                        const size_t off = (size_t)(ik < kMain ? u : u - r) * kVsBytes;
                        bulk_load(dst, gvs + off, nvs, bar, pol);
                        bulk_load(dst + nvs, gvz + off, nvs, bar, pol);
                    }
                    do_k = extra || st == 0;
                    st++;
                    advance(sk, phk);
                } else if (iv < kMain) {
                    mbar_wait(bar_vempty + sv * 8, phv);
                    mbar_expect_tx(bar_vfull + sv * 8, kTile);
                    tensor_load_4d(sb + kOffV + sv * kTile, &map_v, 0, (unit0 + iv * kSplit) * (kTok / 8), bar_vfull + sv * 8, pol);
                    do_k = st < kUnits;
                    iv++;
                    advance(sv, phv);
                } else {
                    mbar_wait(bar_kempty + sk * 8, phk);
                    mbar_expect_tx(bar_kfull + sk * 8, kTile);
                    tensor_load_4d(sb + kOffK + sk * kTile, &map_w, r * 16, (unit0 - r + iv * kSplit) * (kTok / 4),
                                   bar_kfull + sk * 8, pol);
                    iv++;
                    advance(sk, phk);
                }
                if (j == kOpTag) {
                    const uint32_t tag = ((ld_relaxed(prog) / kProgTotal) & 1) ^ 1;
                    asm volatile("st.shared.u32 [%0], %1;" ::"r"(sb + kOffTag), "r"(tag) : "memory");
                }
                if (j == kOps - 24) asm volatile("prefetch.tensormap [%0];" ::"l"(&map_w) : "memory");
            }
        }
        return;
    }

    const int g = lane >> 2, c = lane & 3;
    const int hsel = c >> 1;
    const int ohead = 2 * (c & 1) + hsel;
    const uint32_t* const xg = xch + (size_t)bh * kSplit * kXWords;

    if (warp == kCW + 1) {
        const uint32_t* xoin = pin(xg + kXo + ohead * kD + 16 * r + 2 * g);
        const uint32_t red_rd = pin(sb + kOffRed + lane * 16);
        uint32_t* const optr = pin(reinterpret_cast<uint32_t*>(out + (size_t)(bh * kRep + ohead) * kD + 16 * r + 2 * g));
        asm volatile("bar.sync 0, %0;" ::"n"(kThreads) : "memory");
        mbar_wait(bar_sig, 0);
        const uint32_t tag = lds32(sb + kOffTag);
        uint4 ml;
        int it = 0;
        do {
            ml = ld_relaxed4(xg + g * kXWords + kXm + c * 4);
            if (++it > (1 << 22)) __trap();
        } while (__any_sync(0xffffffffu, stale(ml, tag)));
        float wm[kSplit], we[kSplit];
        {
            const float m = __uint_as_float(ml.x);
            float M = fmaxf(m, __shfl_xor_sync(0xffffffffu, m, 4));
            M = fmaxf(M, __shfl_xor_sync(0xffffffffu, M, 8));
            M = fmaxf(M, __shfl_xor_sync(0xffffffffu, M, 16));
            const float w = ex2(m - M);
            float L = w * __uint_as_float(ml.y);
            L += __shfl_xor_sync(0xffffffffu, L, 4);
            L += __shfl_xor_sync(0xffffffffu, L, 8);
            L += __shfl_xor_sync(0xffffffffu, L, 16);
            const float inv = 1.f / L;
            const float w0 = w * inv, w1 = ex2(__uint_as_float(ml.z) - M) * inv;
#pragma unroll
            for (int k = 0; k < kSplit; k++) {
                wm[k] = __shfl_sync(0xffffffffu, w0, k * 4 + ohead);
                we[k] = __shfl_sync(0xffffffffu, w1, k * 4 + ohead);
            }
        }
        mbar_wait(bar_sig + 8, 0);
        uint2 o[kSplit];
        uint32_t pending = (1u << kSplit) - 1;
        do {
#pragma unroll
            for (int k = 0; k < kSplit; k++)
                if (pending >> k & 1) o[k] = ld_relaxed2(xoin + k * kXWords);
            uint32_t bad = 0;
#pragma unroll
            for (int k = 0; k < kSplit; k++) bad |= (((o[k].x ^ tag) | (o[k].y ^ tag)) & 1) << k;
            pending = __reduce_or_sync(0xffffffffu, bad);
            if (++it > (1 << 22)) __trap();
        } while (pending);
        float y0 = 0.f, y1 = 0.f, u0 = 0.f, u1 = 0.f;
#pragma unroll
        for (int k = 0; k < kSplit; k++) {
            y0 += wm[k] * __uint_as_float(o[k].x);
            y1 += wm[k] * __uint_as_float(o[k].y);
        }
        y0 = pin(y0);
        y1 = pin(y1);
        asm volatile("bar.sync 2, %0;" ::"n"(kCW * 32 + 32) : "memory");
#pragma unroll
        for (int k = 0; k < kCW; k++) {
            const float4 z = lds128f(red_rd + k * 512);
            y0 += we[2 * k] * z.x;
            y1 += we[2 * k] * z.y;
            u0 += we[2 * k + 1] * z.z;
            u1 += we[2 * k + 1] * z.w;
        }
        *optr = pack_bf16(y0 + u0, y1 + u1);
        return;
    }

    const int cw = warp - 1;
    const int par = g & 1;
    uint2 qf[4][2];
    {
        const __nv_bfloat16* qrow = q + (size_t)(bh * kRep + (g & 3)) * kD + 4 * c;
#pragma unroll
        for (int P = 0; P < 4; P++) {
            qf[P][0] = __ldg(reinterpret_cast<const uint2*>(qrow + 32 * P));
            qf[P][1] = __ldg(reinterpret_cast<const uint2*>(qrow + 32 * P + 16));
        }
    }
    const uint32_t k_lane = sb + kOffK + (16 * cw + g) * 512 + c * 16 + par * 64;
    const uint32_t ks_lane = sb + kOffKs + (cw >> 1) * (kD * 2) + c * 8 + par * 32;
    const uint32_t v_lane = sb + kOffV + cw * 1024 + (2 * c) * 128 + ((g ^ (2 * c)) * 16);
    const uint32_t vs_lane = sb + kOffVs + (2 * c) * 2;
    const uint32_t sc_rd = sb + kOffSc + ((g & 3) * 4 + c) * 16;
    const uint32_t sc_wr = sc_rd + cw * 256;
    uint32_t* const xme = xch + (size_t)blockIdx.x * kXWords;
    const bool reporter = threadIdx.x == 32;
    const int gather_at = kStepGather + (blockIdx.x & 31);

    float acc[2][4] = {};
    float m_run = -FLT_MAX, l_run = 0.f, m_pub = 0.f;
    float a0 = 1.f, a1 = 1.f;
    uint32_t pb[4][2] = {};
    uint32_t pn[4][2];
    uint4 pf[kEnd][2][2];
    uint32_t tag = 0;
    int sk = 0, sv = 0, iv = 0;
    uint32_t phk = 0, phv = 0;

    asm volatile("bar.sync 0, %0;" ::"n"(kThreads) : "memory");
#pragma unroll 1
    for (int i = 0; i <= kUnits; i++) {
        if (i < kUnits) {
            mbar_wait(bar_kfull + sk * 8, phk);
            float sa[2][2][4] = {};
#pragma unroll
            for (int P = 0; P < 4; P++)
#pragma unroll
                for (int e = 0; e < 2; e++) {
                    const uint32_t ka = (k_lane ^ (e * 64)) + sk * kTile + P * 128;
                    const uint32_t ksa = (ks_lane ^ (e * 32)) + sk * (2 * kKsBytes) + P * 64;
                    const uint2 zr = lds64(ksa + kKsBytes);
                    const uint2 sc = lds64(ksa);
#pragma unroll
                    for (int u = 0; u < 2; u++) {
                        const int4 x = lds128(ka + u * 8 * 512);
                        mma_bf16(sa[u][e], qf[P][e].x, qf[P][e ^ 1].x, qf[P][e].y, qf[P][e ^ 1].y,
                                 dequant2(x.x, x.y, zr.x, sc.x), dequant2(x.z, x.w, zr.y, sc.y));
                    }
                }
            __syncwarp();
            if (lane == 0) mbar_arrive(bar_kempty + sk * 8);
            if (reporter) red_inc(prog);
            advance(sk, phk);
            if (g < 4) {
                const float2 t0 = logits2(sa[0][0][0] + sa[0][1][0], sa[0][0][3] + sa[0][1][3]);
                const float2 t1 = logits2(sa[1][0][0] + sa[1][1][0], sa[1][0][3] + sa[1][1][3]);
                sts128f(sc_wr + (i & 3) * 1024, t0.x, t0.y, t1.x, t1.y);
            }
            asm volatile("bar.sync 1, %0;" ::"n"(kCW * 32) : "memory");

            float4 t[4];
#pragma unroll
            for (int kk = 0; kk < 4; kk++) t[kk] = lds128f(sc_rd + (i & 3) * 1024 + kk * 256);
            float mx = m_run;
#pragma unroll
            for (int kk = 0; kk < 4; kk++) mx = fmaxf(mx, fmaxf(fmaxf(t[kk].x, t[kk].y), fmaxf(t[kk].z, t[kk].w)));
            mx = fmaxf(mx, __shfl_xor_sync(0xffffffffu, mx, 1));
            mx = fmaxf(mx, __shfl_xor_sync(0xffffffffu, mx, 2));
            const float alpha = ex2(m_run - mx);
            m_run = mx;
            a0 *= __shfl_sync(0xffffffffu, alpha, (c & 1) * 8);
            a1 *= __shfl_sync(0xffffffffu, alpha, (c & 1) * 8 + 4);
            float ls = 0.f;
#pragma unroll
            for (int kk = 0; kk < 4; kk++) {
                const float p0 = ex2(t[kk].x - mx), p1 = ex2(t[kk].y - mx), p2 = ex2(t[kk].z - mx), p3 = ex2(t[kk].w - mx);
                ls += (p0 + p1) + (p2 + p3);
                pn[kk][0] = split_p(p0, p1, g >= 4);
                pn[kk][1] = split_p(p2, p3, g >= 4);
            }
            l_run = l_run * alpha + ls;

            if (i >= kStepEndK && i < kStepEndK + kEnd) {
                if (i == kStepEndK + kEnd - 1) {
                    tag = lds32(sb + kOffTag);
                    m_pub = mx;
                    if (cw < kEnd) {
                        uint32_t w[8];
#pragma unroll
                        for (int kk = 0; kk < 4; kk++) {
                            const float4 u = lds128f(sc_rd + ((kStepEndK + cw) & 3) * 1024 + kk * 256);
                            w[2 * kk] = split_p_tagged(ex2(u.x - mx), ex2(u.y - mx), g >= 4, tag);
                            w[2 * kk + 1] = split_p_tagged(ex2(u.z - mx), ex2(u.w - mx), g >= 4, tag);
                        }
                        st_relaxed4(xme + kXp + cw * 256 + lane * 4, w[0], w[1], w[2], w[3]);
                        st_relaxed4(xme + kXp + cw * 256 + lane * 4 + 128, w[4], w[5], w[6], w[7]);
                    }
                }
                continue;
            }
            if (i == gather_at) {
                int it = 0;
                uint32_t bad;
                do {
#pragma unroll
                    for (int e = 0; e < kEnd; e++)
#pragma unroll
                        for (int s = 0; s < 2; s++)
#pragma unroll
                            for (int h = 0; h < 2; h++)
                                pf[e][s][h] = ld_relaxed4(xg + (2 * cw + s) * kXWords + kXp + e * 256 + h * 128 + lane * 4);
                    bad = 0;
#pragma unroll
                    for (int e = 0; e < kEnd; e++)
#pragma unroll
                        for (int s = 0; s < 2; s++)
#pragma unroll
                            for (int h = 0; h < 2; h++) bad |= stale(pf[e][s][h], tag);
                    if (++it > (1 << 22)) __trap();
                } while (__any_sync(0xffffffffu, bad));
            }
            if (i == kUnits - 1 && cw == kCW - 1) {
                float l = l_run + __shfl_xor_sync(0xffffffffu, l_run, 1);
                l += __shfl_xor_sync(0xffffffffu, l, 2);
                if (c == 0 && g < 4) st_relaxed4(xme + kXm + g * 4, tagged(m_run, tag), tagged(l, tag), tagged(m_pub, tag), tag);
            }
        }
        if (i > 0) {
            const uint32_t va0 = v_lane + sv * kTile, va1 = va0 ^ (128 + 16);
            const uint32_t vsb = vs_lane + (iv & (kVsRing - 1)) * (2 * kVsBytes);
            uint32_t vs[4][2], vz[4][2];
#pragma unroll
            for (int kk = 0; kk < 4; kk++)
#pragma unroll
                for (int u = 0; u < 2; u++) {
                    vs[kk][u] = lds32(vsb + kk * 32 + u * 16);
                    vz[kk][u] = lds32(vsb + kVsBytes + kk * 32 + u * 16);
                }
            mbar_wait(bar_vfull + sv * 8, phv);
#pragma unroll
            for (int kk = 0; kk < 4; kk++) {
                const int4 x0 = lds128(va0 + kk * 8192);
                const int4 x1 = lds128(va1 + kk * 8192);
                const int4 x2 = lds128(va0 + kk * 8192 + 4096);
                const int4 x3 = lds128(va1 + kk * 8192 + 4096);
                mma_bf16(acc[0], dequant2(x0.x, x1.x, vz[kk][0], vs[kk][0]), dequant2(x0.y, x1.y, vz[kk][0], vs[kk][0]),
                         dequant2(x2.x, x3.x, vz[kk][1], vs[kk][1]), dequant2(x2.y, x3.y, vz[kk][1], vs[kk][1]),
                         pb[kk][0], pb[kk][1]);
                mma_bf16(acc[1], dequant2(x0.z, x1.z, vz[kk][0], vs[kk][0]), dequant2(x0.w, x1.w, vz[kk][0], vs[kk][0]),
                         dequant2(x2.z, x3.z, vz[kk][1], vs[kk][1]), dequant2(x2.w, x3.w, vz[kk][1], vs[kk][1]),
                         pb[kk][0], pb[kk][1]);
            }
            __syncwarp();
            if (lane == 0) mbar_arrive(bar_vempty + sv * 8);
            if (reporter) red_inc(prog);
            advance(sv, phv);
            iv++;
        }
#pragma unroll
        for (int m = 0; m < 2; m++) {
            acc[m][0] *= a0;
            acc[m][1] *= a1;
            acc[m][2] *= a0;
            acc[m][3] *= a1;
        }
        a0 = a1 = 1.f;
#pragma unroll
        for (int kk = 0; kk < 4; kk++) {
            pb[kk][0] = pn[kk][0];
            pb[kk][1] = pn[kk][1];
        }
    }

    auto fold = [&](const float (&a)[2][4], float (&y)[4]) {
#pragma unroll
        for (int m = 0; m < 2; m++)
#pragma unroll
            for (int e = 0; e < 2; e++)
                y[2 * m + e] = (hsel ? a[m][2 * e + 1] : a[m][2 * e]) +
                               __shfl_xor_sync(0xffffffffu, hsel ? a[m][2 * e] : a[m][2 * e + 1], 2);
    };
    float y[4];
    fold(acc, y);
    st_relaxed4(xme + kXo + ohead * kD + 32 * cw + 4 * g, tagged(y[0], tag), tagged(y[1], tag), tagged(y[2], tag),
                tagged(y[3], tag));

    const uint32_t w_lane =
        pin(sb + kOffK + cw * 8192 + ((c & 1) + 4 * hsel) * 64 + (((g >> 1) ^ (2 * hsel)) * 16) + (g & 1) * 8);
    const uint32_t red_wr = pin(sb + kOffRed + cw * 512 + lane * 16);
    float a[2][4] = {};
#pragma unroll 1
    for (int e = 0; e < kEnd; e++) {
        const uint32_t wa0 = w_lane + sk * kTile, wa1 = wa0 ^ (128 + 16);
        const uint32_t vsb = sb + kOffVsEnd + (e * kSplit * kTok + cw * 2 * kTok + 2 * c) * 2;
        uint32_t vs[8][2], vz[8][2];
#pragma unroll
        for (int k8 = 0; k8 < 8; k8++)
#pragma unroll
            for (int u = 0; u < 2; u++) {
                vs[k8][u] = lds32(vsb + k8 * 32 + u * 16);
                vz[k8][u] = lds32(vsb + kVsEndBytes + k8 * 32 + u * 16);
            }
        mbar_wait(bar_kfull + sk * 8, phk);
#pragma unroll
        for (int kk = 0; kk < 4; kk++)
#pragma unroll
            for (int s = 0; s < 2; s++) {
                const int k8 = s * 4 + kk;
                const uint2 x0 = lds64(wa0 + k8 * 1024);
                const uint2 x1 = lds64(wa1 + k8 * 1024);
                const uint2 x2 = lds64(wa0 + k8 * 1024 + 512);
                const uint2 x3 = lds64(wa1 + k8 * 1024 + 512);
                const uint4 p = pf[0][s][kk >> 1];
                mma_bf16(a[s], dequant2(x0.x, x1.x, vz[k8][0], vs[k8][0]), dequant2(x0.y, x1.y, vz[k8][0], vs[k8][0]),
                         dequant2(x2.x, x3.x, vz[k8][1], vs[k8][1]), dequant2(x2.y, x3.y, vz[k8][1], vs[k8][1]),
                         (kk & 1) ? p.z : p.x, (kk & 1) ? p.w : p.y);
            }
        if (e == kEnd - 1) break;
        if (reporter) red_inc(prog);
        advance(sk, phk);
#pragma unroll
        for (int n = 0; n + 1 < kEnd; n++)
#pragma unroll
            for (int s = 0; s < 2; s++)
#pragma unroll
                for (int h = 0; h < 2; h++) pf[n][s][h] = pf[n + 1][s][h];
    }
    fold(a, y);
    sts128f(red_wr, y[0], y[1], y[2], y[3]);
    asm volatile("bar.arrive 2, %0;" ::"n"(kCW * 32 + 32) : "memory");
    if (reporter) red_inc(prog);
}

typedef CUresult (*EncodeTiledFn)(CUtensorMap*, CUtensorMapDataType, cuuint32_t, void*, const cuuint64_t*,
                                  const cuuint64_t*, const cuuint32_t*, const cuuint32_t*, CUtensorMapInterleave,
                                  CUtensorMapSwizzle, CUtensorMapL2promotion, CUtensorMapFloatOOBfill);

}

extern "C" void kernel_launch(void* const* d_in, const int* in_sizes, int n_in, void* d_out, int out_size) {
    (void)in_sizes;
    (void)n_in;
    (void)out_size;
    static EncodeTiledFn encode = nullptr;
    static uint32_t* scratch = nullptr;
    if (!encode) {
        cudaGetSymbolAddress((void**)&scratch, g_scratch);
        cudaDriverEntryPointQueryResult qr;
        void* fn = nullptr;
        cudaGetDriverEntryPoint("cuTensorMapEncodeTiled", &fn, cudaEnableDefault, &qr);
        encode = (EncodeTiledFn)fn;
        cudaFuncSetAttribute(kivi_decode_kernel, cudaFuncAttributeMaxDynamicSharedMemorySize, kSmemBytes);
    }
    CUtensorMap map_v, map_w;
    const cuuint32_t estr[4] = {1, 1, 1, 1};
    {
        const cuuint64_t gdim[4] = {32, 8, 4, (cuuint64_t)kBH * kS / 8};
        const cuuint64_t gstr[3] = {512, 128, 4096};
        const cuuint32_t box[4] = {32, 8, 4, kTok / 8};
        encode(&map_v, CU_TENSOR_MAP_DATA_TYPE_INT32, 4, d_in[2], gdim, gstr, box, estr, CU_TENSOR_MAP_INTERLEAVE_NONE,
               CU_TENSOR_MAP_SWIZZLE_128B, CU_TENSOR_MAP_L2_PROMOTION_NONE, CU_TENSOR_MAP_FLOAT_OOB_FILL_NONE);
    }
    {
        const cuuint64_t gdim[4] = {kD, 2, 2, (cuuint64_t)kBH * kS / 4};
        const cuuint64_t gstr[3] = {1024, 512, 2048};
        const cuuint32_t box[4] = {16, 2, 2, kSplit * kTok / 4};
        encode(&map_w, CU_TENSOR_MAP_DATA_TYPE_INT32, 4, d_in[2], gdim, gstr, box, estr, CU_TENSOR_MAP_INTERLEAVE_NONE,
               CU_TENSOR_MAP_SWIZZLE_64B, CU_TENSOR_MAP_L2_PROMOTION_L2_256B, CU_TENSOR_MAP_FLOAT_OOB_FILL_NONE);
    }
    kivi_decode_kernel<<<kCtas, kThreads, kSmemBytes>>>(
        (const int*)d_in[1], (const __nv_bfloat16*)d_in[3], (const __nv_bfloat16*)d_in[4], (const __nv_bfloat16*)d_in[5],
        (const __nv_bfloat16*)d_in[6], (const __nv_bfloat16*)d_in[0], (__nv_bfloat16*)d_out, scratch,
        scratch + kCtas * kXWords, map_v, map_w);
}
```

```cpp
#include <cuda_runtime.h>
#include <cuda_bf16.h>
#include <cuda.h>
#include <stdint.h>
#include <float.h>

namespace {

constexpr int kB = 2, kHq = 32, kHkv = 8, kS = 32768, kD = 128, kG = 32;
constexpr int kRep = kHq / kHkv;
constexpr int kBH = kB * kHkv;
constexpr int kSplit = 8;
constexpr int kCtas = kBH * kSplit;
constexpr int kTok = 64;
constexpr int kUnitsPerBH = kS / kTok;
constexpr int kUnits = kUnitsPerBH / kSplit;
constexpr int kEnd = 3;
constexpr int kMain = kUnits - kEnd;
constexpr int kOps = 2 * kUnits;
constexpr int kStages = 3;
constexpr int kVsRing = 8;
constexpr int kTile = kTok * kD * 4;
constexpr int kKsBytes = (kTok / kG) * kD * 2;
constexpr int kVsBytes = kTok * 2;
constexpr int kVsEndBytes = kEnd * kSplit * kVsBytes;
constexpr int kCW = 4;
constexpr int kThreads = (2 + kCW) * 32;

constexpr int kStepEndK = 14;
constexpr int kStepGather = 22;
constexpr int kOpTag = 16;
constexpr int kOpFetchMl = kOps - 2;
constexpr int kOpFetchO = kOps - 1;
constexpr int kDepth0 = 7 * kCtas, kDepth1 = 23 * kCtas / 8, kRamp0 = 4, kRamp1 = 12;
constexpr uint32_t kProgTotal = kCtas * kOps;
static_assert((kProgTotal & (kProgTotal - 1)) == 0, "progress counter must wrap per launch");
static_assert(kEnd <= kStages && kEnd < kCW && 2 * kStepEndK > kOpTag + 2, "schedule");

constexpr int kXo = 0, kXp = kRep * kD, kXm = kXp + kEnd * 256, kXWords = kXm + 32;

constexpr int kOffK = 0;
constexpr int kOffV = kOffK + kStages * kTile;
constexpr int kOffKs = kOffV + kStages * kTile;
constexpr int kOffVs = kOffKs + kStages * 2 * kKsBytes;
constexpr int kOffVsEnd = kOffVs + kVsRing * 2 * kVsBytes;
constexpr int kOffSc = kOffVsEnd + 2 * kVsEndBytes;
constexpr int kOffRed = kOffSc + 4 * 1024;
constexpr int kOffBar = kOffRed + (kCW + 1) * 512;
constexpr int kOffTag = kOffBar + (4 * kStages + 2) * 8;
constexpr int kSmemBytes = kOffTag + 16 + 1024;

__device__ __align__(128) uint32_t g_scratch[3 << 18];
static_assert(kCtas * kXWords + 32 <= (3 << 18), "scratch");

__device__ __forceinline__ uint32_t smem_u32(const void* p) { return (uint32_t)__cvta_generic_to_shared(p); }
__device__ __forceinline__ bool elect_one() {
    uint32_t p;
    asm volatile("{\n.reg .pred P;\nelect.sync _|P, 0xffffffff;\nselp.u32 %0, 1, 0, P;\n}" : "=r"(p));
    return p != 0;
}
__device__ __forceinline__ void mbar_init(uint32_t bar, uint32_t cnt) {
    asm volatile("mbarrier.init.shared::cta.b64 [%0], %1;" ::"r"(bar), "r"(cnt) : "memory");
}
__device__ __forceinline__ void mbar_expect_tx(uint32_t bar, uint32_t bytes) {
    asm volatile("mbarrier.arrive.expect_tx.shared::cta.b64 _, [%0], %1;" ::"r"(bar), "r"(bytes) : "memory");
}
__device__ __forceinline__ void mbar_arrive(uint32_t bar) {
    asm volatile("mbarrier.arrive.shared::cta.b64 _, [%0];" ::"r"(bar) : "memory");
}
__device__ __forceinline__ void mbar_wait(uint32_t bar, uint32_t parity) {
    uint32_t done;
    int it = 0;
    do {
        asm volatile(
            "{\n.reg .pred p;\nmbarrier.try_wait.parity.shared::cta.b64 p, [%1], %2;\nselp.u32 %0, 1, 0, p;\n}"
            : "=r"(done)
            : "r"(bar), "r"(parity)
            : "memory");
        if (++it > (1 << 24)) __trap();
    } while (!done);
}
__device__ __forceinline__ uint64_t evict_first() {
    uint64_t pol;
    asm volatile("createpolicy.fractional.L2::evict_first.b64 %0, 1.0;" : "=l"(pol));
    return pol;
}
__device__ __forceinline__ void bulk_load(uint32_t dst, const void* src, uint32_t bytes, uint32_t bar, uint64_t pol) {
    asm volatile(
        "cp.async.bulk.shared::cluster.global.mbarrier::complete_tx::bytes.L2::cache_hint [%0], [%1], %2, [%3], %4;" ::"r"(dst),
        "l"(src), "r"(bytes), "r"(bar), "l"(pol)
        : "memory");
}
__device__ __forceinline__ void tensor_load_4d(uint32_t dst, const CUtensorMap* m, int c0, int c3, uint32_t bar, uint64_t pol) {
    asm volatile(
        "cp.async.bulk.tensor.4d.shared::cluster.global.mbarrier::complete_tx::bytes.L2::cache_hint "
        "[%0], [%1, {%3, %4, %4, %5}], [%2], %6;" ::"r"(dst),
        "l"(m), "r"(bar), "r"(c0), "r"(0), "r"(c3), "l"(pol)
        : "memory");
}
__device__ __forceinline__ int4 lds128(uint32_t a) {
    int4 v;
    asm volatile("ld.shared.v4.s32 {%0,%1,%2,%3}, [%4];" : "=r"(v.x), "=r"(v.y), "=r"(v.z), "=r"(v.w) : "r"(a));
    return v;
}
__device__ __forceinline__ float4 lds128f(uint32_t a) {
    float4 v;
    asm volatile("ld.shared.v4.f32 {%0,%1,%2,%3}, [%4];" : "=f"(v.x), "=f"(v.y), "=f"(v.z), "=f"(v.w) : "r"(a));
    return v;
}
__device__ __forceinline__ uint2 lds64(uint32_t a) {
    uint2 v;
    asm volatile("ld.shared.v2.u32 {%0,%1}, [%2];" : "=r"(v.x), "=r"(v.y) : "r"(a));
    return v;
}
__device__ __forceinline__ uint32_t lds32(uint32_t a) {
    uint32_t v;
    asm volatile("ld.shared.u32 %0, [%1];" : "=r"(v) : "r"(a));
    return v;
}
__device__ __forceinline__ void sts128f(uint32_t a, float x, float y, float z, float w) {
    asm volatile("st.shared.v4.f32 [%0], {%1,%2,%3,%4};" ::"r"(a), "f"(x), "f"(y), "f"(z), "f"(w) : "memory");
}
__device__ __forceinline__ uint32_t ld_relaxed(const uint32_t* p) {
    uint32_t v;
    asm volatile("ld.relaxed.gpu.global.u32 %0, [%1];" : "=r"(v) : "l"(p) : "memory");
    return v;
}
__device__ __forceinline__ uint2 ld_relaxed2(const uint32_t* p) {
    uint2 v;
    asm volatile("ld.relaxed.gpu.global.v2.u32 {%0,%1}, [%2];" : "=r"(v.x), "=r"(v.y) : "l"(p) : "memory");
    return v;
}
__device__ __forceinline__ uint4 ld_relaxed4(const uint32_t* p) {
    uint4 v;
    asm volatile("ld.relaxed.gpu.global.v4.u32 {%0,%1,%2,%3}, [%4];" : "=r"(v.x), "=r"(v.y), "=r"(v.z), "=r"(v.w) : "l"(p) : "memory");
    return v;
}
__device__ __forceinline__ void st_relaxed4(uint32_t* p, uint32_t x, uint32_t y, uint32_t z, uint32_t w) {
    asm volatile("st.relaxed.gpu.global.v4.u32 [%0], {%1,%2,%3,%4};" ::"l"(p), "r"(x), "r"(y), "r"(z), "r"(w) : "memory");
}
__device__ __forceinline__ void red_inc(uint32_t* p) {
    asm volatile("red.relaxed.gpu.global.add.u32 [%0], 1;" ::"l"(p) : "memory");
}
__device__ __forceinline__ uint32_t pack_bf16(float lo, float hi) {
    uint32_t r;
    asm("cvt.rn.bf16x2.f32 %0, %1, %2;" : "=r"(r) : "f"(hi), "f"(lo));
    return r;
}
__device__ __forceinline__ float bf16_lo(uint32_t x) { return __uint_as_float(x << 16); }
__device__ __forceinline__ float bf16_hi(uint32_t x) { return __uint_as_float(x & 0xffff0000u); }
__device__ __forceinline__ uint32_t dequant2(int lo, int hi, uint32_t z, uint32_t s) {
    uint32_t x = pack_bf16(__int2float_rn(lo), __int2float_rn(hi));
    uint32_t r;
    asm("sub.rn.bf16x2 %0, %1, %2;" : "=r"(r) : "r"(x), "r"(z));
    asm("mul.rn.bf16x2 %0, %1, %2;" : "=r"(r) : "r"(r), "r"(s));
    return r;
}
__device__ __forceinline__ float2 logits2(float a, float b) {
    const float scale = 0.08838834764831845f, log2e = 1.4426950408889634f;
    uint32_t x = pack_bf16(a, b);
    x = pack_bf16(bf16_lo(x) * scale, bf16_hi(x) * scale);
    return make_float2(bf16_lo(x) * log2e, bf16_hi(x) * log2e);
}
__device__ __forceinline__ void mma_bf16(float (&c)[4], uint32_t a0, uint32_t a1, uint32_t a2, uint32_t a3, uint32_t b0,
                                         uint32_t b1) {
    asm("mma.sync.aligned.m16n8k16.row.col.f32.bf16.bf16.f32 {%0,%1,%2,%3}, {%4,%5,%6,%7}, {%8,%9}, {%0,%1,%2,%3};"
        : "+f"(c[0]), "+f"(c[1]), "+f"(c[2]), "+f"(c[3])
        : "r"(a0), "r"(a1), "r"(a2), "r"(a3), "r"(b0), "r"(b1));
}
__device__ __forceinline__ float ex2(float x) {
    float y;
    asm("ex2.approx.ftz.f32 %0, %1;" : "=f"(y) : "f"(x));
    return y;
}
__device__ __forceinline__ uint32_t split_p(float a, float b, bool lo) {
    uint32_t h = pack_bf16(a, b);
    if (lo) h = pack_bf16(a - bf16_lo(h), b - bf16_hi(h));
    return h;
}
__device__ __forceinline__ uint32_t tagged(uint32_t x, uint32_t tag) { return (x & ~1u) | tag; }
__device__ __forceinline__ uint32_t tagged(float x, uint32_t tag) { return tagged(__float_as_uint(x), tag); }
__device__ __forceinline__ uint32_t split_p_tagged(float a, float b, bool lo, uint32_t tag) {
    uint32_t h = tagged(pack_bf16(a, b), tag);
    if (lo) h = tagged(pack_bf16(a - bf16_lo(h), b - bf16_hi(h)), tag);
    return h;
}
__device__ __forceinline__ uint32_t stale(uint4 v, uint32_t tag) {
    return (((v.x ^ tag) | (v.y ^ tag)) | ((v.z ^ tag) | (v.w ^ tag))) & 1;
}
__device__ __forceinline__ uint32_t pin(uint32_t x) { return __shfl_sync(0xffffffffu, x, threadIdx.x & 31); }
template <typename T>
__device__ __forceinline__ T* pin(T* p) {
    const uint64_t a = reinterpret_cast<uint64_t>(p);
    return reinterpret_cast<T*>((uint64_t)pin((uint32_t)(a >> 32)) << 32 | pin((uint32_t)a));
}
__device__ __forceinline__ void advance(int& s, uint32_t& ph) {
    if (++s == kStages) {
        s = 0;
        ph ^= 1;
    }
}

__global__ void __launch_bounds__(kThreads, 1)
kivi_decode_kernel(const int* __restrict__ qk, const __nv_bfloat16* __restrict__ k_scales,
                   const __nv_bfloat16* __restrict__ k_zeros, const __nv_bfloat16* __restrict__ v_scales,
                   const __nv_bfloat16* __restrict__ v_zeros, const __nv_bfloat16* __restrict__ q,
                   __nv_bfloat16* __restrict__ out, uint32_t* xch, uint32_t* prog,
                   const __grid_constant__ CUtensorMap map_v, const __grid_constant__ CUtensorMap map_w) {
    extern __shared__ uint8_t smem_raw[];
    const int bh = blockIdx.x / kSplit, r = blockIdx.x % kSplit;
    const int unit0 = bh * kUnitsPerBH + r;
    const char* gk = reinterpret_cast<const char*>(qk);
    asm volatile("prefetch.global.L2 [%0];" ::"l"(gk + (size_t)unit0 * kTile + threadIdx.x * 128) : "memory");

    const uint32_t sb = (smem_u32(smem_raw) + 1023u) & ~1023u;
    const uint32_t bar_kfull = sb + kOffBar;
    const uint32_t bar_kempty = bar_kfull + kStages * 8;
    const uint32_t bar_vempty = bar_kempty + kStages * 8;
    const uint32_t bar_vfull = bar_vempty + kStages * 8;
    const uint32_t bar_sig = bar_vfull + kStages * 8;
    if (threadIdx.x < 32) {
        if (elect_one()) {
            const uint64_t pol = evict_first();
            mbar_init(bar_kfull, 1);
            asm volatile("fence.mbarrier_init.release.cluster;" ::: "memory");
            mbar_expect_tx(bar_kfull, kTile + 2 * kKsBytes + 2 * kVsBytes);
            bulk_load(sb + kOffK, gk + (size_t)unit0 * kTile, kTile, bar_kfull, pol);
        }
        __syncwarp();
    }
    const int warp = __shfl_sync(0xffffffffu, threadIdx.x >> 5, 0), lane = threadIdx.x & 31;

    if (warp == 0) {
        if (elect_one()) {
#pragma unroll
            for (int s = 0; s < kStages; s++) {
                if (s) mbar_init(bar_kfull + s * 8, 1);
                mbar_init(bar_kempty + s * 8, kCW);
                mbar_init(bar_vempty + s * 8, kCW);
                mbar_init(bar_vfull + s * 8, 1);
            }
            mbar_init(bar_sig, 1);
            mbar_init(bar_sig + 8, 1);
            asm volatile("fence.mbarrier_init.release.cluster;" ::: "memory");
            asm volatile("prefetch.tensormap [%0];" ::"l"(&map_v) : "memory");
        }
        __syncwarp();
        asm volatile("bar.arrive 0, %0;" ::"n"(kThreads) : "memory");
        if (elect_one()) {
            const uint64_t pol = evict_first();
            const char* gks = reinterpret_cast<const char*>(k_scales);
            const char* gkz = reinterpret_cast<const char*>(k_zeros);
            const char* gvs = reinterpret_cast<const char*>(v_scales);
            const char* gvz = reinterpret_cast<const char*>(v_zeros);
            const int stagger = (int)(__brev(bh) >> 26) - 32;
            uint32_t seen = 0;
            bool pace = true, do_k = true;
            int st = 0, iv = 0, sk = 0, sv = 0;
            uint32_t phk = 1, phv = 1;
#pragma unroll 1
            for (int j = 0; j < kOps; j++) {
                const int depth = j <= kRamp0   ? kDepth0
                                  : j >= kRamp1 ? kDepth1
                                                : kDepth0 + (kDepth1 - kDepth0) / (kRamp1 - kRamp0) * (j - kRamp0);
                const int need = (j + 1) * kCtas - depth + stagger;
                int it = 0;
                while (pace && (int)seen < need) {
                    seen = ld_relaxed(prog) & (kProgTotal - 1);
                    if (++it > 128) pace = false;
                }
                if (j == kOpFetchMl) mbar_arrive(bar_sig);
                if (j == kOpFetchO) mbar_arrive(bar_sig + 8);
                if (do_k) {
                    const bool extra = st >= kStepEndK && st < kStepEndK + kEnd;
                    const int ik = st < kStepEndK ? st : extra ? kMain + st - kStepEndK : st - kEnd;
                    const int u = unit0 + ik * kSplit;
                    const uint32_t bar = bar_kfull + sk * 8;
                    const uint32_t nvs = ik < kMain ? kVsBytes : ik == kMain ? kVsEndBytes : 0;
                    mbar_wait(bar_kempty + sk * 8, phk);
                    if (j) {
                        mbar_expect_tx(bar, kTile + 2 * kKsBytes + 2 * nvs);
                        bulk_load(sb + kOffK + sk * kTile, gk + (size_t)u * kTile, kTile, bar, pol);
                    }
                    bulk_load(sb + kOffKs + sk * 2 * kKsBytes, gks + (size_t)u * kKsBytes, kKsBytes, bar, pol);
                    bulk_load(sb + kOffKs + sk * 2 * kKsBytes + kKsBytes, gkz + (size_t)u * kKsBytes, kKsBytes, bar, pol);
                    if (nvs) {
                        const uint32_t dst = ik < kMain ? sb + kOffVs + (ik & (kVsRing - 1)) * 2 * kVsBytes : sb + kOffVsEnd;
                        const size_t off = (size_t)(ik < kMain ? u : u - r) * kVsBytes;
                        bulk_load(dst, gvs + off, nvs, bar, pol);
                        bulk_load(dst + nvs, gvz + off, nvs, bar, pol);
                    }
                    do_k = extra || st == 0;
                    st++;
                    advance(sk, phk);
                } else if (iv < kMain) {
                    mbar_wait(bar_vempty + sv * 8, phv);
                    mbar_expect_tx(bar_vfull + sv * 8, kTile);
                    tensor_load_4d(sb + kOffV + sv * kTile, &map_v, 0, (unit0 + iv * kSplit) * (kTok / 8), bar_vfull + sv * 8, pol);
                    do_k = st < kUnits;
                    iv++;
                    advance(sv, phv);
                } else {
                    mbar_wait(bar_kempty + sk * 8, phk);
                    mbar_expect_tx(bar_kfull + sk * 8, kTile);
                    tensor_load_4d(sb + kOffK + sk * kTile, &map_w, r * 16, (unit0 - r + iv * kSplit) * (kTok / 4),
                                   bar_kfull + sk * 8, pol);
                    iv++;
                    advance(sk, phk);
                }
                if (j == kOpTag) {
                    const uint32_t tag = ((ld_relaxed(prog) / kProgTotal) & 1) ^ 1;
                    asm volatile("st.shared.u32 [%0], %1;" ::"r"(sb + kOffTag), "r"(tag) : "memory");
                }
                if (j == kOps - 24) asm volatile("prefetch.tensormap [%0];" ::"l"(&map_w) : "memory");
            }
        }
        return;
    }

    const int g = lane >> 2, c = lane & 3;
    const int hsel = c >> 1;
    const int ohead = 2 * (c & 1) + hsel;
    const uint32_t* const xg = xch + (size_t)bh * kSplit * kXWords;

    if (warp == kCW + 1) {
        const uint32_t* xoin = pin(xg + kXo + ohead * kD + 16 * r + 2 * g);
        const uint32_t red_rd = pin(sb + kOffRed + lane * 16);
        uint32_t* const optr = pin(reinterpret_cast<uint32_t*>(out + (size_t)(bh * kRep + ohead) * kD + 16 * r + 2 * g));
        asm volatile("bar.sync 0, %0;" ::"n"(kThreads) : "memory");
        mbar_wait(bar_sig, 0);
        const uint32_t tag = lds32(sb + kOffTag);
        uint4 ml;
        int it = 0;
        do {
            ml = ld_relaxed4(xg + g * kXWords + kXm + c * 4);
            if (++it > (1 << 22)) __trap();
        } while (__any_sync(0xffffffffu, stale(ml, tag)));
        float wm[kSplit], we[kSplit];
        {
            const float m = __uint_as_float(ml.x);
            float M = fmaxf(m, __shfl_xor_sync(0xffffffffu, m, 4));
            M = fmaxf(M, __shfl_xor_sync(0xffffffffu, M, 8));
            M = fmaxf(M, __shfl_xor_sync(0xffffffffu, M, 16));
            const float w = ex2(m - M);
            float L = w * __uint_as_float(ml.y);
            L += __shfl_xor_sync(0xffffffffu, L, 4);
            L += __shfl_xor_sync(0xffffffffu, L, 8);
            L += __shfl_xor_sync(0xffffffffu, L, 16);
            const float inv = 1.f / L;
            const float w0 = w * inv, w1 = ex2(__uint_as_float(ml.z) - M) * inv;
#pragma unroll
            for (int k = 0; k < kSplit; k++) {
                wm[k] = __shfl_sync(0xffffffffu, w0, k * 4 + ohead);
                we[k] = __shfl_sync(0xffffffffu, w1, k * 4 + ohead);
            }
        }
        mbar_wait(bar_sig + 8, 0);
        uint2 o[kSplit];
        uint32_t pending = (1u << kSplit) - 1;
        do {
#pragma unroll
            for (int k = 0; k < kSplit; k++)
                if (pending >> k & 1) o[k] = ld_relaxed2(xoin + k * kXWords);
            uint32_t bad = 0;
#pragma unroll
            for (int k = 0; k < kSplit; k++) bad |= (((o[k].x ^ tag) | (o[k].y ^ tag)) & 1) << k;
            pending = __reduce_or_sync(0xffffffffu, bad);
            if (++it > (1 << 22)) __trap();
        } while (pending);
        float y0 = 0.f, y1 = 0.f, u0 = 0.f, u1 = 0.f;
#pragma unroll
        for (int k = 0; k < kSplit; k++) {
            y0 += wm[k] * __uint_as_float(o[k].x);
            y1 += wm[k] * __uint_as_float(o[k].y);
        }
        if (lane == 0) red_inc(prog);
        sts128f(red_rd + kCW * 512, y0, y1, y0, y1);
        asm volatile("bar.sync 2, %0;" ::"n"(kCW * 32 + 32) : "memory");
#pragma unroll
        for (int k = 0; k < kCW; k++) {
            const float4 z = lds128f(red_rd + k * 512);
            y0 += we[2 * k] * z.x;
            y1 += we[2 * k] * z.y;
            u0 += we[2 * k + 1] * z.z;
            u1 += we[2 * k + 1] * z.w;
        }
        asm volatile("st.global.u32 [%0], %1;" ::"l"(optr), "r"(pack_bf16(y0 + u0, y1 + u1)) : "memory");
        return;
    }

    const int cw = warp - 1;
    const int par = g & 1;
    uint2 qf[4][2];
    {
        const __nv_bfloat16* qrow = q + (size_t)(bh * kRep + (g & 3)) * kD + 4 * c;
#pragma unroll
        for (int P = 0; P < 4; P++) {
            qf[P][0] = __ldg(reinterpret_cast<const uint2*>(qrow + 32 * P));
            qf[P][1] = __ldg(reinterpret_cast<const uint2*>(qrow + 32 * P + 16));
        }
    }
    const uint32_t k_lane = sb + kOffK + (16 * cw + g) * 512 + c * 16 + par * 64;
    const uint32_t ks_lane = sb + kOffKs + (cw >> 1) * (kD * 2) + c * 8 + par * 32;
    const uint32_t v_lane = sb + kOffV + cw * 1024 + (2 * c) * 128 + ((g ^ (2 * c)) * 16);
    const uint32_t vs_lane = sb + kOffVs + (2 * c) * 2;
    const uint32_t sc_rd = sb + kOffSc + ((g & 3) * 4 + c) * 16;
    const uint32_t sc_wr = sc_rd + cw * 256;
    uint32_t* const xme = xch + (size_t)blockIdx.x * kXWords;
    const bool reporter = threadIdx.x == 32;
    const int gather_at = kStepGather + (blockIdx.x & 31);

    float acc[2][4] = {};
    float m_run = -FLT_MAX, l_run = 0.f, m_pub = 0.f;
    float a0 = 1.f, a1 = 1.f;
    uint32_t pb[4][2] = {};
    uint32_t pn[4][2];
    uint4 pf[kEnd][2][2];
    uint32_t tag = 0;
    int sk = 0, sv = 0, iv = 0;
    uint32_t phk = 0, phv = 0;

    asm volatile("bar.sync 0, %0;" ::"n"(kThreads) : "memory");
#pragma unroll 1
    for (int i = 0; i <= kUnits; i++) {
        if (i < kUnits) {
            mbar_wait(bar_kfull + sk * 8, phk);
            float sa[2][2][4] = {};
#pragma unroll
            for (int P = 0; P < 4; P++)
#pragma unroll
                for (int e = 0; e < 2; e++) {
                    const uint32_t ka = (k_lane ^ (e * 64)) + sk * kTile + P * 128;
                    const uint32_t ksa = (ks_lane ^ (e * 32)) + sk * (2 * kKsBytes) + P * 64;
                    const uint2 zr = lds64(ksa + kKsBytes);
                    const uint2 sc = lds64(ksa);
#pragma unroll
                    for (int u = 0; u < 2; u++) {
                        const int4 x = lds128(ka + u * 8 * 512);
                        mma_bf16(sa[u][e], qf[P][e].x, qf[P][e ^ 1].x, qf[P][e].y, qf[P][e ^ 1].y,
                                 dequant2(x.x, x.y, zr.x, sc.x), dequant2(x.z, x.w, zr.y, sc.y));
                    }
                }
            __syncwarp();
            if (lane == 0) mbar_arrive(bar_kempty + sk * 8);
            if (reporter) red_inc(prog);
            advance(sk, phk);
            if (g < 4) {
                const float2 t0 = logits2(sa[0][0][0] + sa[0][1][0], sa[0][0][3] + sa[0][1][3]);
                const float2 t1 = logits2(sa[1][0][0] + sa[1][1][0], sa[1][0][3] + sa[1][1][3]);
                sts128f(sc_wr + (i & 3) * 1024, t0.x, t0.y, t1.x, t1.y);
            }
            asm volatile("bar.sync 1, %0;" ::"n"(kCW * 32) : "memory");

            float4 t[4];
#pragma unroll
            for (int kk = 0; kk < 4; kk++) t[kk] = lds128f(sc_rd + (i & 3) * 1024 + kk * 256);
            float mx = m_run;
#pragma unroll
            for (int kk = 0; kk < 4; kk++) mx = fmaxf(mx, fmaxf(fmaxf(t[kk].x, t[kk].y), fmaxf(t[kk].z, t[kk].w)));
            mx = fmaxf(mx, __shfl_xor_sync(0xffffffffu, mx, 1));
            mx = fmaxf(mx, __shfl_xor_sync(0xffffffffu, mx, 2));
            const float alpha = ex2(m_run - mx);
            m_run = mx;
            a0 *= __shfl_sync(0xffffffffu, alpha, (c & 1) * 8);
            a1 *= __shfl_sync(0xffffffffu, alpha, (c & 1) * 8 + 4);
            float ls = 0.f;
#pragma unroll
            for (int kk = 0; kk < 4; kk++) {
                const float p0 = ex2(t[kk].x - mx), p1 = ex2(t[kk].y - mx), p2 = ex2(t[kk].z - mx), p3 = ex2(t[kk].w - mx);
                ls += (p0 + p1) + (p2 + p3);
                pn[kk][0] = split_p(p0, p1, g >= 4);
                pn[kk][1] = split_p(p2, p3, g >= 4);
            }
            l_run = l_run * alpha + ls;

            if (i >= kStepEndK && i < kStepEndK + kEnd) {
                if (i == kStepEndK + kEnd - 1) {
                    tag = lds32(sb + kOffTag);
                    m_pub = mx;
                    if (cw < kEnd) {
                        uint32_t w[8];
#pragma unroll
                        for (int kk = 0; kk < 4; kk++) {
                            const float4 u = lds128f(sc_rd + ((kStepEndK + cw) & 3) * 1024 + kk * 256);
                            w[2 * kk] = split_p_tagged(ex2(u.x - mx), ex2(u.y - mx), g >= 4, tag);
                            w[2 * kk + 1] = split_p_tagged(ex2(u.z - mx), ex2(u.w - mx), g >= 4, tag);
                        }
                        st_relaxed4(xme + kXp + cw * 256 + lane * 4, w[0], w[1], w[2], w[3]);
                        st_relaxed4(xme + kXp + cw * 256 + lane * 4 + 128, w[4], w[5], w[6], w[7]);
                    }
                }
                continue;
            }
            if (i == gather_at) {
                int it = 0;
                uint32_t bad;
                do {
#pragma unroll
                    for (int e = 0; e < kEnd; e++)
#pragma unroll
                        for (int s = 0; s < 2; s++)
#pragma unroll
                            for (int h = 0; h < 2; h++)
                                pf[e][s][h] = ld_relaxed4(xg + (2 * cw + s) * kXWords + kXp + e * 256 + h * 128 + lane * 4);
                    bad = 0;
#pragma unroll
                    for (int e = 0; e < kEnd; e++)
#pragma unroll
                        for (int s = 0; s < 2; s++)
#pragma unroll
                            for (int h = 0; h < 2; h++) bad |= stale(pf[e][s][h], tag);
                    if (++it > (1 << 22)) __trap();
                } while (__any_sync(0xffffffffu, bad));
            }
            if (i == kUnits - 1 && cw == kCW - 1) {
                float l = l_run + __shfl_xor_sync(0xffffffffu, l_run, 1);
                l += __shfl_xor_sync(0xffffffffu, l, 2);
                if (c == 0 && g < 4) st_relaxed4(xme + kXm + g * 4, tagged(m_run, tag), tagged(l, tag), tagged(m_pub, tag), tag);
            }
        }
        if (i > 0) {
            const uint32_t va0 = v_lane + sv * kTile, va1 = va0 ^ (128 + 16);
            const uint32_t vsb = vs_lane + (iv & (kVsRing - 1)) * (2 * kVsBytes);
            uint32_t vs[4][2], vz[4][2];
#pragma unroll
            for (int kk = 0; kk < 4; kk++)
#pragma unroll
                for (int u = 0; u < 2; u++) {
                    vs[kk][u] = lds32(vsb + kk * 32 + u * 16);
                    vz[kk][u] = lds32(vsb + kVsBytes + kk * 32 + u * 16);
                }
            mbar_wait(bar_vfull + sv * 8, phv);
#pragma unroll
            for (int kk = 0; kk < 4; kk++) {
                const int4 x0 = lds128(va0 + kk * 8192);
                const int4 x1 = lds128(va1 + kk * 8192);
                const int4 x2 = lds128(va0 + kk * 8192 + 4096);
                const int4 x3 = lds128(va1 + kk * 8192 + 4096);
                mma_bf16(acc[0], dequant2(x0.x, x1.x, vz[kk][0], vs[kk][0]), dequant2(x0.y, x1.y, vz[kk][0], vs[kk][0]),
                         dequant2(x2.x, x3.x, vz[kk][1], vs[kk][1]), dequant2(x2.y, x3.y, vz[kk][1], vs[kk][1]),
                         pb[kk][0], pb[kk][1]);
                mma_bf16(acc[1], dequant2(x0.z, x1.z, vz[kk][0], vs[kk][0]), dequant2(x0.w, x1.w, vz[kk][0], vs[kk][0]),
                         dequant2(x2.z, x3.z, vz[kk][1], vs[kk][1]), dequant2(x2.w, x3.w, vz[kk][1], vs[kk][1]),
                         pb[kk][0], pb[kk][1]);
            }
            __syncwarp();
            if (lane == 0) mbar_arrive(bar_vempty + sv * 8);
            if (reporter) red_inc(prog);
            advance(sv, phv);
            iv++;
        }
#pragma unroll
        for (int m = 0; m < 2; m++) {
            acc[m][0] *= a0;
            acc[m][1] *= a1;
            acc[m][2] *= a0;
            acc[m][3] *= a1;
        }
        a0 = a1 = 1.f;
#pragma unroll
        for (int kk = 0; kk < 4; kk++) {
            pb[kk][0] = pn[kk][0];
            pb[kk][1] = pn[kk][1];
        }
    }

    auto fold = [&](const float (&a)[2][4], float (&y)[4]) {
#pragma unroll
        for (int m = 0; m < 2; m++)
#pragma unroll
            for (int e = 0; e < 2; e++)
                y[2 * m + e] = (hsel ? a[m][2 * e + 1] : a[m][2 * e]) +
                               __shfl_xor_sync(0xffffffffu, hsel ? a[m][2 * e] : a[m][2 * e + 1], 2);
    };
    float y[4];
    fold(acc, y);
    st_relaxed4(xme + kXo + ohead * kD + 32 * cw + 4 * g, tagged(y[0], tag), tagged(y[1], tag), tagged(y[2], tag),
                tagged(y[3], tag));

    const uint32_t w_lane =
        pin(sb + kOffK + cw * 8192 + ((c & 1) + 4 * hsel) * 64 + (((g >> 1) ^ (2 * hsel)) * 16) + (g & 1) * 8);
    const uint32_t red_wr = pin(sb + kOffRed + cw * 512 + lane * 16);
    float a[2][4] = {};
#pragma unroll 1
    for (int e = 0; e < kEnd; e++) {
        const uint32_t wa0 = w_lane + sk * kTile, wa1 = wa0 ^ (128 + 16);
        const uint32_t vsb = sb + kOffVsEnd + (e * kSplit * kTok + cw * 2 * kTok + 2 * c) * 2;
        uint32_t vs[8][2], vz[8][2];
#pragma unroll
        for (int k8 = 0; k8 < 8; k8++)
#pragma unroll
            for (int u = 0; u < 2; u++) {
                vs[k8][u] = lds32(vsb + k8 * 32 + u * 16);
                vz[k8][u] = lds32(vsb + kVsEndBytes + k8 * 32 + u * 16);
            }
        mbar_wait(bar_kfull + sk * 8, phk);
#pragma unroll
        for (int kk = 0; kk < 4; kk++)
#pragma unroll
            for (int s = 0; s < 2; s++) {
                const int k8 = s * 4 + kk;
                const uint2 x0 = lds64(wa0 + k8 * 1024);
                const uint2 x1 = lds64(wa1 + k8 * 1024);
                const uint2 x2 = lds64(wa0 + k8 * 1024 + 512);
                const uint2 x3 = lds64(wa1 + k8 * 1024 + 512);
                const uint4 p = pf[0][s][kk >> 1];
                mma_bf16(a[s], dequant2(x0.x, x1.x, vz[k8][0], vs[k8][0]), dequant2(x0.y, x1.y, vz[k8][0], vs[k8][0]),
                         dequant2(x2.x, x3.x, vz[k8][1], vs[k8][1]), dequant2(x2.y, x3.y, vz[k8][1], vs[k8][1]),
                         (kk & 1) ? p.z : p.x, (kk & 1) ? p.w : p.y);
            }
        if (e == kEnd - 1) break;
        if (reporter) red_inc(prog);
        advance(sk, phk);
#pragma unroll
        for (int n = 0; n + 1 < kEnd; n++)
#pragma unroll
            for (int s = 0; s < 2; s++)
#pragma unroll
                for (int h = 0; h < 2; h++) pf[n][s][h] = pf[n + 1][s][h];
    }
    fold(a, y);
    sts128f(red_wr, y[0], y[1], y[2], y[3]);
    asm volatile("bar.arrive 2, %0;" ::"n"(kCW * 32 + 32) : "memory");
}

typedef CUresult (*EncodeTiledFn)(CUtensorMap*, CUtensorMapDataType, cuuint32_t, void*, const cuuint64_t*,
                                  const cuuint64_t*, const cuuint32_t*, const cuuint32_t*, CUtensorMapInterleave,
                                  CUtensorMapSwizzle, CUtensorMapL2promotion, CUtensorMapFloatOOBfill);

}

extern "C" void kernel_launch(void* const* d_in, const int* in_sizes, int n_in, void* d_out, int out_size) {
    (void)in_sizes;
    (void)n_in;
    (void)out_size;
    static EncodeTiledFn encode = nullptr;
    static uint32_t* scratch = nullptr;
    if (!encode) {
        cudaGetSymbolAddress((void**)&scratch, g_scratch);
        cudaDriverEntryPointQueryResult qr;
        void* fn = nullptr;
        cudaGetDriverEntryPoint("cuTensorMapEncodeTiled", &fn, cudaEnableDefault, &qr);
        encode = (EncodeTiledFn)fn;
        cudaFuncSetAttribute(kivi_decode_kernel, cudaFuncAttributeMaxDynamicSharedMemorySize, kSmemBytes);
    }
    CUtensorMap map_v, map_w;
    const cuuint32_t estr[4] = {1, 1, 1, 1};
    {
        const cuuint64_t gdim[4] = {32, 8, 4, (cuuint64_t)kBH * kS / 8};
        const cuuint64_t gstr[3] = {512, 128, 4096};
        const cuuint32_t box[4] = {32, 8, 4, kTok / 8};
        encode(&map_v, CU_TENSOR_MAP_DATA_TYPE_INT32, 4, d_in[2], gdim, gstr, box, estr, CU_TENSOR_MAP_INTERLEAVE_NONE,
               CU_TENSOR_MAP_SWIZZLE_128B, CU_TENSOR_MAP_L2_PROMOTION_NONE, CU_TENSOR_MAP_FLOAT_OOB_FILL_NONE);
    }
    {
        const cuuint64_t gdim[4] = {kD, 2, 2, (cuuint64_t)kBH * kS / 4};
        const cuuint64_t gstr[3] = {1024, 512, 2048};
        const cuuint32_t box[4] = {16, 2, 2, kSplit * kTok / 4};
        encode(&map_w, CU_TENSOR_MAP_DATA_TYPE_INT32, 4, d_in[2], gdim, gstr, box, estr, CU_TENSOR_MAP_INTERLEAVE_NONE,
               CU_TENSOR_MAP_SWIZZLE_64B, CU_TENSOR_MAP_L2_PROMOTION_L2_256B, CU_TENSOR_MAP_FLOAT_OOB_FILL_NONE);
    }
    kivi_decode_kernel<<<kCtas, kThreads, kSmemBytes>>>(
        (const int*)d_in[1], (const __nv_bfloat16*)d_in[3], (const __nv_bfloat16*)d_in[4], (const __nv_bfloat16*)d_in[5],
        (const __nv_bfloat16*)d_in[6], (const __nv_bfloat16*)d_in[0], (__nv_bfloat16*)d_out, scratch,
        scratch + kCtas * kXWords, map_v, map_w);
}
```

```cpp
#include <cuda_runtime.h>
#include <cuda_bf16.h>
#include <cuda.h>
#include <stdint.h>
#include <float.h>

namespace {

constexpr int kB = 2, kHq = 32, kHkv = 8, kS = 32768, kD = 128, kG = 32;
constexpr int kRep = kHq / kHkv;
constexpr int kBH = kB * kHkv;
constexpr int kSplit = 8;
constexpr int kCtas = kBH * kSplit;
constexpr int kTok = 64;
constexpr int kUnitsPerBH = kS / kTok;
constexpr int kUnits = kUnitsPerBH / kSplit;
constexpr int kEnd = 3;
constexpr int kMain = kUnits - kEnd;
constexpr int kOps = 2 * kUnits;
constexpr int kStages = 3;
constexpr int kVsRing = 8;
constexpr int kTile = kTok * kD * 4;
constexpr int kKsBytes = (kTok / kG) * kD * 2;
constexpr int kVsBytes = kTok * 2;
constexpr int kVsEndBytes = kEnd * kSplit * kVsBytes;
constexpr int kCW = 4;
constexpr int kThreads = (2 + kCW) * 32;

constexpr int kStepEndK = 14;
constexpr int kStepGather = 22;
constexpr int kOpFetchMl = kOps - 2;
constexpr int kOpFetchO = kOps - 1;
constexpr int kDepth0 = 7 * kCtas, kDepth1 = 23 * kCtas / 8, kRamp0 = 4, kRamp1 = 12;
constexpr uint32_t kProgTotal = kCtas * kOps;
static_assert(kEnd <= kStages && kEnd < kCW, "schedule");

constexpr int kXo = 0, kXp = kRep * kD, kXm = kXp + kEnd * 256, kXWords = kXm + 32;

constexpr int kOffK = 0;
constexpr int kOffV = kOffK + kStages * kTile;
constexpr int kOffKs = kOffV + kStages * kTile;
constexpr int kOffVs = kOffKs + kStages * 2 * kKsBytes;
constexpr int kOffVsEnd = kOffVs + kVsRing * 2 * kVsBytes;
constexpr int kOffSc = kOffVsEnd + 2 * kVsEndBytes;
constexpr int kOffRed = kOffSc + 4 * 1024;
constexpr int kOffBar = kOffRed + (kCW + 1) * 512;
constexpr int kOffTag = kOffBar + (4 * kStages + 2) * 8;
constexpr int kSmemBytes = kOffTag + 16 + 1024;

constexpr int kScrProg = kCtas * kXWords, kScrEpoch = kScrProg + 32;
__device__ __align__(128) uint32_t g_scratch[3 << 18];
static_assert(kScrEpoch + kCtas <= (3 << 18), "scratch");

__device__ __forceinline__ uint32_t smem_u32(const void* p) { return (uint32_t)__cvta_generic_to_shared(p); }
__device__ __forceinline__ bool elect_one() {
    uint32_t p;
    asm volatile("{\n.reg .pred P;\nelect.sync _|P, 0xffffffff;\nselp.u32 %0, 1, 0, P;\n}" : "=r"(p));
    return p != 0;
}
__device__ __forceinline__ void mbar_init(uint32_t bar, uint32_t cnt) {
    asm volatile("mbarrier.init.shared::cta.b64 [%0], %1;" ::"r"(bar), "r"(cnt) : "memory");
}
__device__ __forceinline__ void mbar_expect_tx(uint32_t bar, uint32_t bytes) {
    asm volatile("mbarrier.arrive.expect_tx.shared::cta.b64 _, [%0], %1;" ::"r"(bar), "r"(bytes) : "memory");
}
__device__ __forceinline__ void mbar_arrive(uint32_t bar) {
    asm volatile("mbarrier.arrive.shared::cta.b64 _, [%0];" ::"r"(bar) : "memory");
}
__device__ __forceinline__ void mbar_wait(uint32_t bar, uint32_t parity) {
    uint32_t done;
    int it = 0;
    do {
        asm volatile(
            "{\n.reg .pred p;\nmbarrier.try_wait.parity.shared::cta.b64 p, [%1], %2;\nselp.u32 %0, 1, 0, p;\n}"
            : "=r"(done)
            : "r"(bar), "r"(parity)
            : "memory");
        if (++it > (1 << 24)) __trap();
    } while (!done);
}
__device__ __forceinline__ uint64_t evict_first() {
    uint64_t pol;
    asm volatile("createpolicy.fractional.L2::evict_first.b64 %0, 1.0;" : "=l"(pol));
    return pol;
}
__device__ __forceinline__ void bulk_load(uint32_t dst, const void* src, uint32_t bytes, uint32_t bar, uint64_t pol) {
    asm volatile(
        "cp.async.bulk.shared::cluster.global.mbarrier::complete_tx::bytes.L2::cache_hint [%0], [%1], %2, [%3], %4;" ::"r"(dst),
        "l"(src), "r"(bytes), "r"(bar), "l"(pol)
        : "memory");
}
__device__ __forceinline__ void tensor_load_4d(uint32_t dst, const CUtensorMap* m, int c0, int c3, uint32_t bar, uint64_t pol) {
    asm volatile(
        "cp.async.bulk.tensor.4d.shared::cluster.global.mbarrier::complete_tx::bytes.L2::cache_hint "
        "[%0], [%1, {%3, %4, %4, %5}], [%2], %6;" ::"r"(dst),
        "l"(m), "r"(bar), "r"(c0), "r"(0), "r"(c3), "l"(pol)
        : "memory");
}
__device__ __forceinline__ int4 lds128(uint32_t a) {
    int4 v;
    asm volatile("ld.shared.v4.s32 {%0,%1,%2,%3}, [%4];" : "=r"(v.x), "=r"(v.y), "=r"(v.z), "=r"(v.w) : "r"(a));
    return v;
}
__device__ __forceinline__ float4 lds128f(uint32_t a) {
    float4 v;
    asm volatile("ld.shared.v4.f32 {%0,%1,%2,%3}, [%4];" : "=f"(v.x), "=f"(v.y), "=f"(v.z), "=f"(v.w) : "r"(a));
    return v;
}
__device__ __forceinline__ uint2 lds64(uint32_t a) {
    uint2 v;
    asm volatile("ld.shared.v2.u32 {%0,%1}, [%2];" : "=r"(v.x), "=r"(v.y) : "r"(a));
    return v;
}
__device__ __forceinline__ uint32_t lds32(uint32_t a) {
    uint32_t v;
    asm volatile("ld.shared.u32 %0, [%1];" : "=r"(v) : "r"(a));
    return v;
}
__device__ __forceinline__ void sts128f(uint32_t a, float x, float y, float z, float w) {
    asm volatile("st.shared.v4.f32 [%0], {%1,%2,%3,%4};" ::"r"(a), "f"(x), "f"(y), "f"(z), "f"(w) : "memory");
}
__device__ __forceinline__ uint32_t ld_relaxed(const uint32_t* p) {
    uint32_t v;
    asm volatile("ld.relaxed.gpu.global.u32 %0, [%1];" : "=r"(v) : "l"(p) : "memory");
    return v;
}
__device__ __forceinline__ uint2 ld_relaxed2(const uint32_t* p) {
    uint2 v;
    asm volatile("ld.relaxed.gpu.global.v2.u32 {%0,%1}, [%2];" : "=r"(v.x), "=r"(v.y) : "l"(p) : "memory");
    return v;
}
__device__ __forceinline__ uint4 ld_relaxed4(const uint32_t* p) {
    uint4 v;
    asm volatile("ld.relaxed.gpu.global.v4.u32 {%0,%1,%2,%3}, [%4];" : "=r"(v.x), "=r"(v.y), "=r"(v.z), "=r"(v.w) : "l"(p) : "memory");
    return v;
}
__device__ __forceinline__ void st_relaxed4(uint32_t* p, uint32_t x, uint32_t y, uint32_t z, uint32_t w) {
    asm volatile("st.relaxed.gpu.global.v4.u32 [%0], {%1,%2,%3,%4};" ::"l"(p), "r"(x), "r"(y), "r"(z), "r"(w) : "memory");
}
__device__ __forceinline__ void tick(uint32_t* prog) {
    asm volatile("red.relaxed.gpu.global.inc.u32 [%0], %1;" ::"l"(prog), "n"(kProgTotal - 1) : "memory");
}
__device__ __forceinline__ uint32_t pack_bf16(float lo, float hi) {
    uint32_t r;
    asm("cvt.rn.bf16x2.f32 %0, %1, %2;" : "=r"(r) : "f"(hi), "f"(lo));
    return r;
}
__device__ __forceinline__ float bf16_lo(uint32_t x) { return __uint_as_float(x << 16); }
__device__ __forceinline__ float bf16_hi(uint32_t x) { return __uint_as_float(x & 0xffff0000u); }
__device__ __forceinline__ uint32_t dequant2(int lo, int hi, uint32_t z, uint32_t s) {
    uint32_t x = pack_bf16(__int2float_rn(lo), __int2float_rn(hi));
    uint32_t r;
    asm("sub.rn.bf16x2 %0, %1, %2;" : "=r"(r) : "r"(x), "r"(z));
    asm("mul.rn.bf16x2 %0, %1, %2;" : "=r"(r) : "r"(r), "r"(s));
    return r;
}
__device__ __forceinline__ float2 logits2(float a, float b) {
    const float scale = 0.08838834764831845f, log2e = 1.4426950408889634f;
    uint32_t x = pack_bf16(a, b);
    x = pack_bf16(bf16_lo(x) * scale, bf16_hi(x) * scale);
    return make_float2(bf16_lo(x) * log2e, bf16_hi(x) * log2e);
}
__device__ __forceinline__ void mma_bf16(float (&c)[4], uint32_t a0, uint32_t a1, uint32_t a2, uint32_t a3, uint32_t b0,
                                         uint32_t b1) {
    asm("mma.sync.aligned.m16n8k16.row.col.f32.bf16.bf16.f32 {%0,%1,%2,%3}, {%4,%5,%6,%7}, {%8,%9}, {%0,%1,%2,%3};"
        : "+f"(c[0]), "+f"(c[1]), "+f"(c[2]), "+f"(c[3])
        : "r"(a0), "r"(a1), "r"(a2), "r"(a3), "r"(b0), "r"(b1));
}
__device__ __forceinline__ float ex2(float x) {
    float y;
    asm("ex2.approx.ftz.f32 %0, %1;" : "=f"(y) : "f"(x));
    return y;
}
__device__ __forceinline__ uint32_t split_p(float a, float b, bool lo) {
    uint32_t h = pack_bf16(a, b);
    if (lo) h = pack_bf16(a - bf16_lo(h), b - bf16_hi(h));
    return h;
}
__device__ __forceinline__ uint32_t tagged(uint32_t x, uint32_t tag) { return (x & ~1u) | tag; }
__device__ __forceinline__ uint32_t tagged(float x, uint32_t tag) { return tagged(__float_as_uint(x), tag); }
__device__ __forceinline__ uint32_t split_p_tagged(float a, float b, bool lo, uint32_t tag) {
    uint32_t h = tagged(pack_bf16(a, b), tag);
    if (lo) h = tagged(pack_bf16(a - bf16_lo(h), b - bf16_hi(h)), tag);
    return h;
}
__device__ __forceinline__ uint32_t stale(uint4 v, uint32_t tag) {
    return (((v.x ^ tag) | (v.y ^ tag)) | ((v.z ^ tag) | (v.w ^ tag))) & 1;
}
__device__ __forceinline__ uint32_t pin(uint32_t x) { return __shfl_sync(0xffffffffu, x, threadIdx.x & 31); }
template <typename T>
__device__ __forceinline__ T* pin(T* p) {
    const uint64_t a = reinterpret_cast<uint64_t>(p);
    return reinterpret_cast<T*>((uint64_t)pin((uint32_t)(a >> 32)) << 32 | pin((uint32_t)a));
}
__device__ __forceinline__ void advance(int& s, uint32_t& ph) {
    if (++s == kStages) {
        s = 0;
        ph ^= 1;
    }
}

__global__ void __launch_bounds__(kThreads, 1)
kivi_decode_kernel(const int* __restrict__ qk, const __nv_bfloat16* __restrict__ k_scales,
                   const __nv_bfloat16* __restrict__ k_zeros, const __nv_bfloat16* __restrict__ v_scales,
                   const __nv_bfloat16* __restrict__ v_zeros, const __nv_bfloat16* __restrict__ q,
                   __nv_bfloat16* __restrict__ out, uint32_t* xch,
                   const __grid_constant__ CUtensorMap map_v, const __grid_constant__ CUtensorMap map_w) {
    extern __shared__ uint8_t smem_raw[];
    const int bh = blockIdx.x / kSplit, r = blockIdx.x % kSplit;
    const int unit0 = bh * kUnitsPerBH + r;
    const char* gk = reinterpret_cast<const char*>(qk);
    asm volatile("prefetch.global.L2 [%0];" ::"l"(gk + (size_t)unit0 * kTile + threadIdx.x * 128) : "memory");

    const uint32_t sb = (smem_u32(smem_raw) + 1023u) & ~1023u;
    const uint32_t bar_kfull = sb + kOffBar;
    const uint32_t bar_kempty = bar_kfull + kStages * 8;
    const uint32_t bar_vempty = bar_kempty + kStages * 8;
    const uint32_t bar_vfull = bar_vempty + kStages * 8;
    const uint32_t bar_sig = bar_vfull + kStages * 8;
    if (threadIdx.x < 32) {
        if (elect_one()) {
            const uint64_t pol = evict_first();
            mbar_init(bar_kfull, 1);
            asm volatile("fence.mbarrier_init.release.cluster;" ::: "memory");
            mbar_expect_tx(bar_kfull, kTile + 2 * kKsBytes + 2 * kVsBytes);
            bulk_load(sb + kOffK, gk + (size_t)unit0 * kTile, kTile, bar_kfull, pol);
        }
        __syncwarp();
    }
    const int warp = __shfl_sync(0xffffffffu, threadIdx.x >> 5, 0), lane = threadIdx.x & 31;
    uint32_t* const prog = xch + kScrProg;

    if (warp == 0) {
        if (elect_one()) {
#pragma unroll
            for (int s = 0; s < kStages; s++) {
                if (s) mbar_init(bar_kfull + s * 8, 1);
                mbar_init(bar_kempty + s * 8, kCW);
                mbar_init(bar_vempty + s * 8, kCW);
                mbar_init(bar_vfull + s * 8, 1);
            }
            mbar_init(bar_sig, 1);
            mbar_init(bar_sig + 8, 1);
            asm volatile("fence.mbarrier_init.release.cluster;" ::: "memory");
            asm volatile("prefetch.tensormap [%0];" ::"l"(&map_v) : "memory");
        }
        __syncwarp();
        asm volatile("bar.arrive 0, %0;" ::"n"(kThreads) : "memory");
        if (elect_one()) {
            const uint64_t pol = evict_first();
            const char* gks = reinterpret_cast<const char*>(k_scales);
            const char* gkz = reinterpret_cast<const char*>(k_zeros);
            const char* gvs = reinterpret_cast<const char*>(v_scales);
            const char* gvz = reinterpret_cast<const char*>(v_zeros);
            const int stagger = (int)(__brev(bh) >> 26) - 32;
            uint32_t seen = 0;
            bool pace = true, do_k = true;
            int st = 0, iv = 0, sk = 0, sv = 0;
            uint32_t phk = 1, phv = 1;
#pragma unroll 1
            for (int j = 0; j < kOps; j++) {
                const int depth = j <= kRamp0   ? kDepth0
                                  : j >= kRamp1 ? kDepth1
                                                : kDepth0 + (kDepth1 - kDepth0) / (kRamp1 - kRamp0) * (j - kRamp0);
                const int need = (j + 1) * kCtas - depth + stagger;
                int it = 0;
                while (pace && (int)seen < need) {
                    seen = ld_relaxed(prog);
                    if (++it > 128) pace = false;
                }
                if (j == kOpFetchMl) mbar_arrive(bar_sig);
                if (j == kOpFetchO) mbar_arrive(bar_sig + 8);
                if (do_k) {
                    const bool extra = st >= kStepEndK && st < kStepEndK + kEnd;
                    const int ik = st < kStepEndK ? st : extra ? kMain + st - kStepEndK : st - kEnd;
                    const int u = unit0 + ik * kSplit;
                    const uint32_t bar = bar_kfull + sk * 8;
                    const uint32_t nvs = ik < kMain ? kVsBytes : ik == kMain ? kVsEndBytes : 0;
                    mbar_wait(bar_kempty + sk * 8, phk);
                    if (j) {
                        mbar_expect_tx(bar, kTile + 2 * kKsBytes + 2 * nvs);
                        bulk_load(sb + kOffK + sk * kTile, gk + (size_t)u * kTile, kTile, bar, pol);
                    }
                    bulk_load(sb + kOffKs + sk * 2 * kKsBytes, gks + (size_t)u * kKsBytes, kKsBytes, bar, pol);
                    bulk_load(sb + kOffKs + sk * 2 * kKsBytes + kKsBytes, gkz + (size_t)u * kKsBytes, kKsBytes, bar, pol);
                    if (nvs) {
                        const uint32_t dst = ik < kMain ? sb + kOffVs + (ik & (kVsRing - 1)) * 2 * kVsBytes : sb + kOffVsEnd;
                        const size_t off = (size_t)(ik < kMain ? u : u - r) * kVsBytes;
                        bulk_load(dst, gvs + off, nvs, bar, pol);
                        bulk_load(dst + nvs, gvz + off, nvs, bar, pol);
                    }
                    do_k = extra || st == 0;
                    st++;
                    advance(sk, phk);
                } else if (iv < kMain) {
                    mbar_wait(bar_vempty + sv * 8, phv);
                    mbar_expect_tx(bar_vfull + sv * 8, kTile);
                    tensor_load_4d(sb + kOffV + sv * kTile, &map_v, 0, (unit0 + iv * kSplit) * (kTok / 8), bar_vfull + sv * 8, pol);
                    do_k = st < kUnits;
                    iv++;
                    advance(sv, phv);
                } else {
                    mbar_wait(bar_kempty + sk * 8, phk);
                    mbar_expect_tx(bar_kfull + sk * 8, kTile);
                    tensor_load_4d(sb + kOffK + sk * kTile, &map_w, r * 16, (unit0 - r + iv * kSplit) * (kTok / 4),
                                   bar_kfull + sk * 8, pol);
                    iv++;
                    advance(sk, phk);
                }
                if (j == kOps - 24) asm volatile("prefetch.tensormap [%0];" ::"l"(&map_w) : "memory");
            }
        }
        return;
    }

    const int g = lane >> 2, c = lane & 3;
    const int hsel = c >> 1;
    const int ohead = 2 * (c & 1) + hsel;
    const uint32_t* const xg = xch + (size_t)bh * kSplit * kXWords;

    if (warp == kCW + 1) {
        const uint32_t* xoin = pin(xg + kXo + ohead * kD + 16 * r + 2 * g);
        const uint32_t red_rd = pin(sb + kOffRed + lane * 16);
        uint32_t* const optr = pin(reinterpret_cast<uint32_t*>(out + (size_t)(bh * kRep + ohead) * kD + 16 * r + 2 * g));
        const uint32_t epoch = ld_relaxed(xch + kScrEpoch + blockIdx.x) + 1;
        const uint32_t tag = epoch & 1;
        __syncwarp();
        if (lane == 0) {
            asm volatile("st.shared.u32 [%0], %1;" ::"r"(sb + kOffTag), "r"(tag) : "memory");
            xch[kScrEpoch + blockIdx.x] = epoch;
        }
        asm volatile("bar.sync 0, %0;" ::"n"(kThreads) : "memory");
        mbar_wait(bar_sig, 0);
        uint4 ml;
        int it = 0;
        do {
            ml = ld_relaxed4(xg + g * kXWords + kXm + c * 4);
            if (++it > (1 << 22)) __trap();
        } while (__any_sync(0xffffffffu, stale(ml, tag)));
        float wm[kSplit], we[kSplit];
        {
            const float m = __uint_as_float(ml.x);
            float M = fmaxf(m, __shfl_xor_sync(0xffffffffu, m, 4));
            M = fmaxf(M, __shfl_xor_sync(0xffffffffu, M, 8));
            M = fmaxf(M, __shfl_xor_sync(0xffffffffu, M, 16));
            const float w = ex2(m - M);
            float L = w * __uint_as_float(ml.y);
            L += __shfl_xor_sync(0xffffffffu, L, 4);
            L += __shfl_xor_sync(0xffffffffu, L, 8);
            L += __shfl_xor_sync(0xffffffffu, L, 16);
            const float inv = 1.f / L;
            const float w0 = w * inv, w1 = ex2(__uint_as_float(ml.z) - M) * inv;
#pragma unroll
            for (int k = 0; k < kSplit; k++) {
                wm[k] = __shfl_sync(0xffffffffu, w0, k * 4 + ohead);
                we[k] = __shfl_sync(0xffffffffu, w1, k * 4 + ohead);
            }
        }
        mbar_wait(bar_sig + 8, 0);
        uint2 o[kSplit];
        uint32_t pending = (1u << kSplit) - 1;
        do {
#pragma unroll
            for (int k = 0; k < kSplit; k++)
                if (pending >> k & 1) o[k] = ld_relaxed2(xoin + k * kXWords);
            uint32_t bad = 0;
#pragma unroll
            for (int k = 0; k < kSplit; k++) bad |= (((o[k].x ^ tag) | (o[k].y ^ tag)) & 1) << k;
            pending = __reduce_or_sync(0xffffffffu, bad);
            if (++it > (1 << 22)) __trap();
        } while (pending);
        float y0 = 0.f, y1 = 0.f, u0 = 0.f, u1 = 0.f;
#pragma unroll
        for (int k = 0; k < kSplit; k++) {
            y0 += wm[k] * __uint_as_float(o[k].x);
            y1 += wm[k] * __uint_as_float(o[k].y);
        }
        if (lane == 0) tick(prog);
        sts128f(red_rd + kCW * 512, y0, y1, y0, y1);
        asm volatile("bar.sync 2, %0;" ::"n"(kCW * 32 + 32) : "memory");
#pragma unroll
        for (int k = 0; k < kCW; k++) {
            const float4 z = lds128f(red_rd + k * 512);
            y0 += we[2 * k] * z.x;
            y1 += we[2 * k] * z.y;
            u0 += we[2 * k + 1] * z.z;
            u1 += we[2 * k + 1] * z.w;
        }
        asm volatile("st.global.u32 [%0], %1;" ::"l"(optr), "r"(pack_bf16(y0 + u0, y1 + u1)) : "memory");
        return;
    }

    const int cw = warp - 1;
    const int par = g & 1;
    uint2 qf[4][2];
    {
        const __nv_bfloat16* qrow = q + (size_t)(bh * kRep + (g & 3)) * kD + 4 * c;
#pragma unroll
        for (int P = 0; P < 4; P++) {
            qf[P][0] = __ldg(reinterpret_cast<const uint2*>(qrow + 32 * P));
            qf[P][1] = __ldg(reinterpret_cast<const uint2*>(qrow + 32 * P + 16));
        }
    }
    const uint32_t k_lane = sb + kOffK + (16 * cw + g) * 512 + c * 16 + par * 64;
    const uint32_t ks_lane = sb + kOffKs + (cw >> 1) * (kD * 2) + c * 8 + par * 32;
    const uint32_t v_lane = sb + kOffV + cw * 1024 + (2 * c) * 128 + ((g ^ (2 * c)) * 16);
    const uint32_t vs_lane = sb + kOffVs + (2 * c) * 2;
    const uint32_t sc_rd = sb + kOffSc + ((g & 3) * 4 + c) * 16;
    const uint32_t sc_wr = sc_rd + cw * 256;
    uint32_t* const xme = xch + (size_t)blockIdx.x * kXWords;
    const bool reporter = threadIdx.x == 32;
    const int gather_at = kStepGather + (blockIdx.x & 31);

    float acc[2][4] = {};
    float m_run = -FLT_MAX, l_run = 0.f, m_pub = 0.f;
    float a0 = 1.f, a1 = 1.f;
    uint32_t pb[4][2] = {};
    uint32_t pn[4][2];
    uint4 pf[kEnd][2][2];
    int sk = 0, sv = 0, iv = 0;
    uint32_t phk = 0, phv = 0;

    asm volatile("bar.sync 0, %0;" ::"n"(kThreads) : "memory");
    const uint32_t tag = lds32(sb + kOffTag);
#pragma unroll 1
    for (int i = 0; i <= kUnits; i++) {
        if (i < kUnits) {
            mbar_wait(bar_kfull + sk * 8, phk);
            float sa[2][2][4] = {};
#pragma unroll
            for (int P = 0; P < 4; P++)
#pragma unroll
                for (int e = 0; e < 2; e++) {
                    const uint32_t ka = (k_lane ^ (e * 64)) + sk * kTile + P * 128;
                    const uint32_t ksa = (ks_lane ^ (e * 32)) + sk * (2 * kKsBytes) + P * 64;
                    const uint2 zr = lds64(ksa + kKsBytes);
                    const uint2 sc = lds64(ksa);
#pragma unroll
                    for (int u = 0; u < 2; u++) {
                        const int4 x = lds128(ka + u * 8 * 512);
                        mma_bf16(sa[u][e], qf[P][e].x, qf[P][e ^ 1].x, qf[P][e].y, qf[P][e ^ 1].y,
                                 dequant2(x.x, x.y, zr.x, sc.x), dequant2(x.z, x.w, zr.y, sc.y));
                    }
                }
            __syncwarp();
            if (lane == 0) mbar_arrive(bar_kempty + sk * 8);
            if (reporter) tick(prog);
            advance(sk, phk);
            if (g < 4) {
                const float2 t0 = logits2(sa[0][0][0] + sa[0][1][0], sa[0][0][3] + sa[0][1][3]);
                const float2 t1 = logits2(sa[1][0][0] + sa[1][1][0], sa[1][0][3] + sa[1][1][3]);
                sts128f(sc_wr + (i & 3) * 1024, t0.x, t0.y, t1.x, t1.y);
            }
            asm volatile("bar.sync 1, %0;" ::"n"(kCW * 32) : "memory");

            float4 t[4];
#pragma unroll
            for (int kk = 0; kk < 4; kk++) t[kk] = lds128f(sc_rd + (i & 3) * 1024 + kk * 256);
            float mx = m_run;
#pragma unroll
            for (int kk = 0; kk < 4; kk++) mx = fmaxf(mx, fmaxf(fmaxf(t[kk].x, t[kk].y), fmaxf(t[kk].z, t[kk].w)));
            mx = fmaxf(mx, __shfl_xor_sync(0xffffffffu, mx, 1));
            mx = fmaxf(mx, __shfl_xor_sync(0xffffffffu, mx, 2));
            const float alpha = ex2(m_run - mx);
            m_run = mx;
            a0 *= __shfl_sync(0xffffffffu, alpha, (c & 1) * 8);
            a1 *= __shfl_sync(0xffffffffu, alpha, (c & 1) * 8 + 4);
            float ls = 0.f;
#pragma unroll
            for (int kk = 0; kk < 4; kk++) {
                const float p0 = ex2(t[kk].x - mx), p1 = ex2(t[kk].y - mx), p2 = ex2(t[kk].z - mx), p3 = ex2(t[kk].w - mx);
                ls += (p0 + p1) + (p2 + p3);
                pn[kk][0] = split_p(p0, p1, g >= 4);
                pn[kk][1] = split_p(p2, p3, g >= 4);
            }
            l_run = l_run * alpha + ls;

            if (i >= kStepEndK && i < kStepEndK + kEnd) {
                if (i == kStepEndK + kEnd - 1) {
                    m_pub = mx;
                    if (cw < kEnd) {
                        uint32_t w[8];
#pragma unroll
                        for (int kk = 0; kk < 4; kk++) {
                            const float4 u = lds128f(sc_rd + ((kStepEndK + cw) & 3) * 1024 + kk * 256);
                            w[2 * kk] = split_p_tagged(ex2(u.x - mx), ex2(u.y - mx), g >= 4, tag);
                            w[2 * kk + 1] = split_p_tagged(ex2(u.z - mx), ex2(u.w - mx), g >= 4, tag);
                        }
                        st_relaxed4(xme + kXp + cw * 256 + lane * 4, w[0], w[1], w[2], w[3]);
                        st_relaxed4(xme + kXp + cw * 256 + lane * 4 + 128, w[4], w[5], w[6], w[7]);
                    }
                }
                continue;
            }
            if (i == gather_at) {
                int it = 0;
                uint32_t bad;
                do {
#pragma unroll
                    for (int e = 0; e < kEnd; e++)
#pragma unroll
                        for (int s = 0; s < 2; s++)
#pragma unroll
                            for (int h = 0; h < 2; h++)
                                pf[e][s][h] = ld_relaxed4(xg + (2 * cw + s) * kXWords + kXp + e * 256 + h * 128 + lane * 4);
                    bad = 0;
#pragma unroll
                    for (int e = 0; e < kEnd; e++)
#pragma unroll
                        for (int s = 0; s < 2; s++)
#pragma unroll
                            for (int h = 0; h < 2; h++) bad |= stale(pf[e][s][h], tag);
                    if (++it > (1 << 22)) __trap();
                } while (__any_sync(0xffffffffu, bad));
            }
            if (i == kUnits - 1 && cw == kCW - 1) {
                float l = l_run + __shfl_xor_sync(0xffffffffu, l_run, 1);
                l += __shfl_xor_sync(0xffffffffu, l, 2);
                if (c == 0 && g < 4) st_relaxed4(xme + kXm + g * 4, tagged(m_run, tag), tagged(l, tag), tagged(m_pub, tag), tag);
            }
        }
        if (i > 0) {
            const uint32_t va0 = v_lane + sv * kTile, va1 = va0 ^ (128 + 16);
            const uint32_t vsb = vs_lane + (iv & (kVsRing - 1)) * (2 * kVsBytes);
            uint32_t vs[4][2], vz[4][2];
#pragma unroll
            for (int kk = 0; kk < 4; kk++)
#pragma unroll
                for (int u = 0; u < 2; u++) {
                    vs[kk][u] = lds32(vsb + kk * 32 + u * 16);
                    vz[kk][u] = lds32(vsb + kVsBytes + kk * 32 + u * 16);
                }
            mbar_wait(bar_vfull + sv * 8, phv);
#pragma unroll
            for (int kk = 0; kk < 4; kk++) {
                const int4 x0 = lds128(va0 + kk * 8192);
                const int4 x1 = lds128(va1 + kk * 8192);
                const int4 x2 = lds128(va0 + kk * 8192 + 4096);
                const int4 x3 = lds128(va1 + kk * 8192 + 4096);
                mma_bf16(acc[0], dequant2(x0.x, x1.x, vz[kk][0], vs[kk][0]), dequant2(x0.y, x1.y, vz[kk][0], vs[kk][0]),
                         dequant2(x2.x, x3.x, vz[kk][1], vs[kk][1]), dequant2(x2.y, x3.y, vz[kk][1], vs[kk][1]),
                         pb[kk][0], pb[kk][1]);
                mma_bf16(acc[1], dequant2(x0.z, x1.z, vz[kk][0], vs[kk][0]), dequant2(x0.w, x1.w, vz[kk][0], vs[kk][0]),
                         dequant2(x2.z, x3.z, vz[kk][1], vs[kk][1]), dequant2(x2.w, x3.w, vz[kk][1], vs[kk][1]),
                         pb[kk][0], pb[kk][1]);
            }
            __syncwarp();
            if (lane == 0) mbar_arrive(bar_vempty + sv * 8);
            if (reporter) tick(prog);
            advance(sv, phv);
            iv++;
        }
#pragma unroll
        for (int m = 0; m < 2; m++) {
            acc[m][0] *= a0;
            acc[m][1] *= a1;
            acc[m][2] *= a0;
            acc[m][3] *= a1;
        }
        a0 = a1 = 1.f;
#pragma unroll
        for (int kk = 0; kk < 4; kk++) {
            pb[kk][0] = pn[kk][0];
            pb[kk][1] = pn[kk][1];
        }
    }

    auto fold = [&](const float (&a)[2][4], float (&y)[4]) {
#pragma unroll
        for (int m = 0; m < 2; m++)
#pragma unroll
            for (int e = 0; e < 2; e++)
                y[2 * m + e] = (hsel ? a[m][2 * e + 1] : a[m][2 * e]) +
                               __shfl_xor_sync(0xffffffffu, hsel ? a[m][2 * e] : a[m][2 * e + 1], 2);
    };
    float y[4];
    fold(acc, y);
    st_relaxed4(xme + kXo + ohead * kD + 32 * cw + 4 * g, tagged(y[0], tag), tagged(y[1], tag), tagged(y[2], tag),
                tagged(y[3], tag));

    const uint32_t w_lane =
        pin(sb + kOffK + cw * 8192 + ((c & 1) + 4 * hsel) * 64 + (((g >> 1) ^ (2 * hsel)) * 16) + (g & 1) * 8);
    const uint32_t red_wr = pin(sb + kOffRed + cw * 512 + lane * 16);
    float a[2][4] = {};
#pragma unroll 1
    for (int e = 0; e < kEnd; e++) {
        const uint32_t wa0 = w_lane + sk * kTile, wa1 = wa0 ^ (128 + 16);
        const uint32_t vsb = sb + kOffVsEnd + (e * kSplit * kTok + cw * 2 * kTok + 2 * c) * 2;
        uint32_t vs[8][2], vz[8][2];
#pragma unroll
        for (int k8 = 0; k8 < 8; k8++)
#pragma unroll
            for (int u = 0; u < 2; u++) {
                vs[k8][u] = lds32(vsb + k8 * 32 + u * 16);
                vz[k8][u] = lds32(vsb + kVsEndBytes + k8 * 32 + u * 16);
            }
        mbar_wait(bar_kfull + sk * 8, phk);
#pragma unroll
        for (int kk = 0; kk < 4; kk++)
#pragma unroll
            for (int s = 0; s < 2; s++) {
                const int k8 = s * 4 + kk;
                const uint2 x0 = lds64(wa0 + k8 * 1024);
                const uint2 x1 = lds64(wa1 + k8 * 1024);
                const uint2 x2 = lds64(wa0 + k8 * 1024 + 512);
                const uint2 x3 = lds64(wa1 + k8 * 1024 + 512);
                const uint4 p = pf[0][s][kk >> 1];
                mma_bf16(a[s], dequant2(x0.x, x1.x, vz[k8][0], vs[k8][0]), dequant2(x0.y, x1.y, vz[k8][0], vs[k8][0]),
                         dequant2(x2.x, x3.x, vz[k8][1], vs[k8][1]), dequant2(x2.y, x3.y, vz[k8][1], vs[k8][1]),
                         (kk & 1) ? p.z : p.x, (kk & 1) ? p.w : p.y);
            }
        if (e == kEnd - 1) break;
        if (reporter) tick(prog);
        advance(sk, phk);
#pragma unroll
        for (int n = 0; n + 1 < kEnd; n++)
#pragma unroll
            for (int s = 0; s < 2; s++)
#pragma unroll
                for (int h = 0; h < 2; h++) pf[n][s][h] = pf[n + 1][s][h];
    }
    fold(a, y);
    sts128f(red_wr, y[0], y[1], y[2], y[3]);
    asm volatile("bar.arrive 2, %0;" ::"n"(kCW * 32 + 32) : "memory");
}

typedef CUresult (*EncodeTiledFn)(CUtensorMap*, CUtensorMapDataType, cuuint32_t, void*, const cuuint64_t*,
                                  const cuuint64_t*, const cuuint32_t*, const cuuint32_t*, CUtensorMapInterleave,
                                  CUtensorMapSwizzle, CUtensorMapL2promotion, CUtensorMapFloatOOBfill);

}

extern "C" void kernel_launch(void* const* d_in, const int* in_sizes, int n_in, void* d_out, int out_size) {
    (void)in_sizes;
    (void)n_in;
    (void)out_size;
    static EncodeTiledFn encode = nullptr;
    static uint32_t* scratch = nullptr;
    if (!encode) {
        cudaGetSymbolAddress((void**)&scratch, g_scratch);
        cudaDriverEntryPointQueryResult qr;
        void* fn = nullptr;
        cudaGetDriverEntryPoint("cuTensorMapEncodeTiled", &fn, cudaEnableDefault, &qr);
        encode = (EncodeTiledFn)fn;
        cudaFuncSetAttribute(kivi_decode_kernel, cudaFuncAttributeMaxDynamicSharedMemorySize, kSmemBytes);
    }
    CUtensorMap map_v, map_w;
    const cuuint32_t estr[4] = {1, 1, 1, 1};
    {
        const cuuint64_t gdim[4] = {32, 8, 4, (cuuint64_t)kBH * kS / 8};
        const cuuint64_t gstr[3] = {512, 128, 4096};
        const cuuint32_t box[4] = {32, 8, 4, kTok / 8};
        encode(&map_v, CU_TENSOR_MAP_DATA_TYPE_INT32, 4, d_in[2], gdim, gstr, box, estr, CU_TENSOR_MAP_INTERLEAVE_NONE,
               CU_TENSOR_MAP_SWIZZLE_128B, CU_TENSOR_MAP_L2_PROMOTION_NONE, CU_TENSOR_MAP_FLOAT_OOB_FILL_NONE);
    }
    {
        const cuuint64_t gdim[4] = {kD, 2, 2, (cuuint64_t)kBH * kS / 4};
        const cuuint64_t gstr[3] = {1024, 512, 2048};
        const cuuint32_t box[4] = {16, 2, 2, kSplit * kTok / 4};
        encode(&map_w, CU_TENSOR_MAP_DATA_TYPE_INT32, 4, d_in[2], gdim, gstr, box, estr, CU_TENSOR_MAP_INTERLEAVE_NONE,
               CU_TENSOR_MAP_SWIZZLE_64B, CU_TENSOR_MAP_L2_PROMOTION_L2_256B, CU_TENSOR_MAP_FLOAT_OOB_FILL_NONE);
    }
    kivi_decode_kernel<<<kCtas, kThreads, kSmemBytes>>>(
        (const int*)d_in[1], (const __nv_bfloat16*)d_in[3], (const __nv_bfloat16*)d_in[4], (const __nv_bfloat16*)d_in[5],
        (const __nv_bfloat16*)d_in[6], (const __nv_bfloat16*)d_in[0], (__nv_bfloat16*)d_out, scratch, map_v, map_w);
}
```

```cpp
#include <cuda_runtime.h>
#include <cuda_bf16.h>
#include <cuda.h>
#include <stdint.h>
#include <float.h>

namespace {

constexpr int kB = 2, kHq = 32, kHkv = 8, kS = 32768, kD = 128, kG = 32;
constexpr int kRep = kHq / kHkv;
constexpr int kBH = kB * kHkv;
constexpr int kSplit = 8;
constexpr int kCtas = kBH * kSplit;
constexpr int kTok = 64;
constexpr int kUnitsPerBH = kS / kTok;
constexpr int kUnits = kUnitsPerBH / kSplit;
constexpr int kEnd = 3;
constexpr int kMain = kUnits - kEnd;
constexpr int kOps = 2 * kUnits;
constexpr int kStages = 3;
constexpr int kVsRing = 8;
constexpr int kTile = kTok * kD * 4;
constexpr int kKsBytes = (kTok / kG) * kD * 2;
constexpr int kVsBytes = kTok * 2;
constexpr int kVsEndBytes = kEnd * kSplit * kVsBytes;
constexpr int kCW = 4;
constexpr int kThreads = (2 + kCW) * 32;

constexpr int kStepEndK = 14;
constexpr int kStepGather = 22;
constexpr int kOpFetchMl = kOps - 2;
constexpr int kOpFetchO = kOps - 1;
constexpr int kDepth0 = 7 * kCtas, kDepth1 = 23 * kCtas / 8, kRamp0 = 4, kRamp1 = 12;
constexpr uint32_t kProgTotal = kCtas * kOps;
static_assert(kEnd <= kStages && kEnd < kCW, "schedule");

constexpr int kXo = 0, kXp = kRep * kD, kXm = kXp + kEnd * 256, kXWords = kXm + 32;

constexpr int kOffK = 0;
constexpr int kOffV = kOffK + kStages * kTile;
constexpr int kOffKs = kOffV + kStages * kTile;
constexpr int kOffVs = kOffKs + kStages * 2 * kKsBytes;
constexpr int kOffVsEnd = kOffVs + kVsRing * 2 * kVsBytes;
constexpr int kOffSc = kOffVsEnd + 2 * kVsEndBytes;
constexpr int kOffRed = kOffSc + 4 * 1024;
constexpr int kOffBar = kOffRed + (kCW + 1) * 512;
constexpr int kOffTag = kOffBar + (4 * kStages + 2) * 8;
constexpr int kSmemBytes = kOffTag + 16 + 1024;

constexpr int kScrProg = kCtas * kXWords, kScrEpoch = kScrProg + 32;
__device__ __align__(128) uint32_t g_scratch[3 << 18];
static_assert(kScrEpoch + kCtas <= (3 << 18), "scratch");

__device__ __forceinline__ uint32_t smem_u32(const void* p) { return (uint32_t)__cvta_generic_to_shared(p); }
__device__ __forceinline__ bool elect_one() {
    uint32_t p;
    asm volatile("{\n.reg .pred P;\nelect.sync _|P, 0xffffffff;\nselp.u32 %0, 1, 0, P;\n}" : "=r"(p));
    return p != 0;
}
__device__ __forceinline__ void mbar_init(uint32_t bar, uint32_t cnt) {
    asm volatile("mbarrier.init.shared::cta.b64 [%0], %1;" ::"r"(bar), "r"(cnt) : "memory");
}
__device__ __forceinline__ void mbar_expect_tx(uint32_t bar, uint32_t bytes) {
    asm volatile("mbarrier.arrive.expect_tx.shared::cta.b64 _, [%0], %1;" ::"r"(bar), "r"(bytes) : "memory");
}
__device__ __forceinline__ void mbar_arrive(uint32_t bar) {
    asm volatile("mbarrier.arrive.shared::cta.b64 _, [%0];" ::"r"(bar) : "memory");
}
__device__ __forceinline__ void mbar_wait(uint32_t bar, uint32_t parity) {
    uint32_t done;
    int it = 0;
    do {
        asm volatile(
            "{\n.reg .pred p;\nmbarrier.try_wait.parity.shared::cta.b64 p, [%1], %2;\nselp.u32 %0, 1, 0, p;\n}"
            : "=r"(done)
            : "r"(bar), "r"(parity)
            : "memory");
        if (++it > (1 << 24)) __trap();
    } while (!done);
}
__device__ __forceinline__ uint64_t evict_first() {
    uint64_t pol;
    asm volatile("createpolicy.fractional.L2::evict_first.b64 %0, 1.0;" : "=l"(pol));
    return pol;
}
__device__ __forceinline__ void bulk_load(uint32_t dst, const void* src, uint32_t bytes, uint32_t bar, uint64_t pol) {
    asm volatile(
        "cp.async.bulk.shared::cluster.global.mbarrier::complete_tx::bytes.L2::cache_hint [%0], [%1], %2, [%3], %4;" ::"r"(dst),
        "l"(src), "r"(bytes), "r"(bar), "l"(pol)
        : "memory");
}
__device__ __forceinline__ void tensor_load_4d(uint32_t dst, const CUtensorMap* m, int c0, int c3, uint32_t bar, uint64_t pol) {
    asm volatile(
        "cp.async.bulk.tensor.4d.shared::cluster.global.mbarrier::complete_tx::bytes.L2::cache_hint "
        "[%0], [%1, {%3, %4, %4, %5}], [%2], %6;" ::"r"(dst),
        "l"(m), "r"(bar), "r"(c0), "r"(0), "r"(c3), "l"(pol)
        : "memory");
}
__device__ __forceinline__ int4 lds128(uint32_t a) {
    int4 v;
    asm volatile("ld.shared.v4.s32 {%0,%1,%2,%3}, [%4];" : "=r"(v.x), "=r"(v.y), "=r"(v.z), "=r"(v.w) : "r"(a));
    return v;
}
__device__ __forceinline__ float4 lds128f(uint32_t a) {
    float4 v;
    asm volatile("ld.shared.v4.f32 {%0,%1,%2,%3}, [%4];" : "=f"(v.x), "=f"(v.y), "=f"(v.z), "=f"(v.w) : "r"(a));
    return v;
}
__device__ __forceinline__ uint2 lds64(uint32_t a) {
    uint2 v;
    asm volatile("ld.shared.v2.u32 {%0,%1}, [%2];" : "=r"(v.x), "=r"(v.y) : "r"(a));
    return v;
}
__device__ __forceinline__ uint32_t lds32(uint32_t a) {
    uint32_t v;
    asm volatile("ld.shared.u32 %0, [%1];" : "=r"(v) : "r"(a));
    return v;
}
__device__ __forceinline__ void sts128f(uint32_t a, float x, float y, float z, float w) {
    asm volatile("st.shared.v4.f32 [%0], {%1,%2,%3,%4};" ::"r"(a), "f"(x), "f"(y), "f"(z), "f"(w) : "memory");
}
__device__ __forceinline__ uint32_t ld_relaxed(const uint32_t* p) {
    uint32_t v;
    asm volatile("ld.relaxed.gpu.global.u32 %0, [%1];" : "=r"(v) : "l"(p) : "memory");
    return v;
}
__device__ __forceinline__ uint2 ld_relaxed2(const uint32_t* p) {
    uint2 v;
    asm volatile("ld.relaxed.gpu.global.v2.u32 {%0,%1}, [%2];" : "=r"(v.x), "=r"(v.y) : "l"(p) : "memory");
    return v;
}
__device__ __forceinline__ uint4 ld_relaxed4(const uint32_t* p) {
    uint4 v;
    asm volatile("ld.relaxed.gpu.global.v4.u32 {%0,%1,%2,%3}, [%4];" : "=r"(v.x), "=r"(v.y), "=r"(v.z), "=r"(v.w) : "l"(p) : "memory");
    return v;
}
__device__ __forceinline__ void st_relaxed4(uint32_t* p, uint32_t x, uint32_t y, uint32_t z, uint32_t w) {
    asm volatile("st.relaxed.gpu.global.v4.u32 [%0], {%1,%2,%3,%4};" ::"l"(p), "r"(x), "r"(y), "r"(z), "r"(w) : "memory");
}
__device__ __forceinline__ void tick(uint32_t* prog) {
    asm volatile("red.relaxed.gpu.global.inc.u32 [%0], %1;" ::"l"(prog), "n"(kProgTotal - 1) : "memory");
}
__device__ __forceinline__ uint32_t pack_bf16(float lo, float hi) {
    uint32_t r;
    asm("cvt.rn.bf16x2.f32 %0, %1, %2;" : "=r"(r) : "f"(hi), "f"(lo));
    return r;
}
__device__ __forceinline__ float bf16_lo(uint32_t x) { return __uint_as_float(x << 16); }
__device__ __forceinline__ float bf16_hi(uint32_t x) { return __uint_as_float(x & 0xffff0000u); }
__device__ __forceinline__ uint32_t dequant2(int lo, int hi, uint32_t z, uint32_t s) {
    uint32_t x = pack_bf16(__int2float_rn(lo), __int2float_rn(hi));
    uint32_t r;
    asm("sub.rn.bf16x2 %0, %1, %2;" : "=r"(r) : "r"(x), "r"(z));
    asm("mul.rn.bf16x2 %0, %1, %2;" : "=r"(r) : "r"(r), "r"(s));
    return r;
}
__device__ __forceinline__ float2 logits2(float a, float b) {
    const float scale = 0.08838834764831845f, log2e = 1.4426950408889634f;
    uint32_t x = pack_bf16(a, b);
    x = pack_bf16(bf16_lo(x) * scale, bf16_hi(x) * scale);
    return make_float2(bf16_lo(x) * log2e, bf16_hi(x) * log2e);
}
__device__ __forceinline__ void mma_bf16(float (&c)[4], uint32_t a0, uint32_t a1, uint32_t a2, uint32_t a3, uint32_t b0,
                                         uint32_t b1) {
    asm("mma.sync.aligned.m16n8k16.row.col.f32.bf16.bf16.f32 {%0,%1,%2,%3}, {%4,%5,%6,%7}, {%8,%9}, {%0,%1,%2,%3};"
        : "+f"(c[0]), "+f"(c[1]), "+f"(c[2]), "+f"(c[3])
        : "r"(a0), "r"(a1), "r"(a2), "r"(a3), "r"(b0), "r"(b1));
}
__device__ __forceinline__ float ex2(float x) {
    float y;
    asm("ex2.approx.ftz.f32 %0, %1;" : "=f"(y) : "f"(x));
    return y;
}
__device__ __forceinline__ uint32_t split_p(float a, float b, bool lo) {
    uint32_t h = pack_bf16(a, b);
    if (lo) h = pack_bf16(a - bf16_lo(h), b - bf16_hi(h));
    return h;
}
__device__ __forceinline__ uint32_t tagged(float x, uint32_t tag) { return (__float_as_uint(x) & ~1u) | tag; }
__device__ __forceinline__ float untagged(uint32_t x) { return __uint_as_float(x & ~1u); }
__device__ __forceinline__ uint32_t split_p_tagged(float a, float b, bool lo, uint32_t tag) {
    uint32_t h = pack_bf16(a, b) & ~1u;
    if (lo) h = pack_bf16(a - bf16_lo(h), b - bf16_hi(h)) & ~1u;
    return h | tag;
}
__device__ __forceinline__ uint32_t stale(uint4 v, uint32_t tag) {
    return (((v.x ^ tag) | (v.y ^ tag)) | ((v.z ^ tag) | (v.w ^ tag))) & 1;
}
__device__ __forceinline__ uint32_t pin(uint32_t x) { return __shfl_sync(0xffffffffu, x, threadIdx.x & 31); }
template <typename T>
__device__ __forceinline__ T* pin(T* p) {
    const uint64_t a = reinterpret_cast<uint64_t>(p);
    return reinterpret_cast<T*>((uint64_t)pin((uint32_t)(a >> 32)) << 32 | pin((uint32_t)a));
}
__device__ __forceinline__ void advance(int& s, uint32_t& ph) {
    if (++s == kStages) {
        s = 0;
        ph ^= 1;
    }
}

__global__ void __launch_bounds__(kThreads, 1)
kivi_decode_kernel(const int* __restrict__ qk, const __nv_bfloat16* __restrict__ k_scales,
                   const __nv_bfloat16* __restrict__ k_zeros, const __nv_bfloat16* __restrict__ v_scales,
                   const __nv_bfloat16* __restrict__ v_zeros, const __nv_bfloat16* __restrict__ q,
                   __nv_bfloat16* __restrict__ out, uint32_t* xch,
                   const __grid_constant__ CUtensorMap map_v, const __grid_constant__ CUtensorMap map_w) {
    extern __shared__ uint8_t smem_raw[];
    const int bh = blockIdx.x / kSplit, r = blockIdx.x % kSplit;
    const int unit0 = bh * kUnitsPerBH + r;
    const char* gk = reinterpret_cast<const char*>(qk);
    asm volatile("prefetch.global.L2 [%0];" ::"l"(gk + (size_t)unit0 * kTile + threadIdx.x * 128) : "memory");

    const uint32_t sb = (smem_u32(smem_raw) + 1023u) & ~1023u;
    const uint32_t bar_kfull = sb + kOffBar;
    const uint32_t bar_kempty = bar_kfull + kStages * 8;
    const uint32_t bar_vempty = bar_kempty + kStages * 8;
    const uint32_t bar_vfull = bar_vempty + kStages * 8;
    const uint32_t bar_sig = bar_vfull + kStages * 8;
    if (threadIdx.x < 32) {
        if (elect_one()) {
            const uint64_t pol = evict_first();
            mbar_init(bar_kfull, 1);
            asm volatile("fence.mbarrier_init.release.cluster;" ::: "memory");
            mbar_expect_tx(bar_kfull, kTile + 2 * kKsBytes + 2 * kVsBytes);
            bulk_load(sb + kOffK, gk + (size_t)unit0 * kTile, kTile, bar_kfull, pol);
        }
        __syncwarp();
    }
    const int warp = __shfl_sync(0xffffffffu, threadIdx.x >> 5, 0), lane = threadIdx.x & 31;
    uint32_t* const prog = xch + kScrProg;

    if (warp == 0) {
        if (elect_one()) {
#pragma unroll
            for (int s = 0; s < kStages; s++) {
                if (s) mbar_init(bar_kfull + s * 8, 1);
                mbar_init(bar_kempty + s * 8, kCW);
                mbar_init(bar_vempty + s * 8, kCW);
                mbar_init(bar_vfull + s * 8, 1);
            }
            mbar_init(bar_sig, 1);
            mbar_init(bar_sig + 8, 1);
            asm volatile("fence.mbarrier_init.release.cluster;" ::: "memory");
            asm volatile("prefetch.tensormap [%0];" ::"l"(&map_v) : "memory");
        }
        __syncwarp();
        asm volatile("bar.arrive 0, %0;" ::"n"(kThreads) : "memory");
        if (elect_one()) {
            const uint64_t pol = evict_first();
            const char* gks = reinterpret_cast<const char*>(k_scales);
            const char* gkz = reinterpret_cast<const char*>(k_zeros);
            const char* gvs = reinterpret_cast<const char*>(v_scales);
            const char* gvz = reinterpret_cast<const char*>(v_zeros);
            const int stagger = (int)(__brev(bh) >> 26) - 32;
            uint32_t seen = 0;
            bool pace = true, do_k = true;
            int st = 0, iv = 0, sk = 0, sv = 0;
            uint32_t phk = 1, phv = 1;
#pragma unroll 1
            for (int j = 0; j < kOps; j++) {
                const int depth = j <= kRamp0   ? kDepth0
                                  : j >= kRamp1 ? kDepth1
                                                : kDepth0 + (kDepth1 - kDepth0) / (kRamp1 - kRamp0) * (j - kRamp0);
                const int need = (j + 1) * kCtas - depth + stagger;
                int it = 0;
                while (pace && (int)seen < need) {
                    seen = ld_relaxed(prog);
                    if (++it > 128) pace = false;
                }
                if (j == kOpFetchMl) mbar_arrive(bar_sig);
                if (j == kOpFetchO) mbar_arrive(bar_sig + 8);
                if (do_k) {
                    const bool extra = st >= kStepEndK && st < kStepEndK + kEnd;
                    const int ik = st < kStepEndK ? st : extra ? kMain + st - kStepEndK : st - kEnd;
                    const int u = unit0 + ik * kSplit;
                    const uint32_t bar = bar_kfull + sk * 8;
                    const uint32_t nvs = ik < kMain ? kVsBytes : ik == kMain ? kVsEndBytes : 0;
                    mbar_wait(bar_kempty + sk * 8, phk);
                    if (j) {
                        mbar_expect_tx(bar, kTile + 2 * kKsBytes + 2 * nvs);
                        bulk_load(sb + kOffK + sk * kTile, gk + (size_t)u * kTile, kTile, bar, pol);
                    }
                    bulk_load(sb + kOffKs + sk * 2 * kKsBytes, gks + (size_t)u * kKsBytes, kKsBytes, bar, pol);
                    bulk_load(sb + kOffKs + sk * 2 * kKsBytes + kKsBytes, gkz + (size_t)u * kKsBytes, kKsBytes, bar, pol);
                    if (nvs) {
                        const uint32_t dst = ik < kMain ? sb + kOffVs + (ik & (kVsRing - 1)) * 2 * kVsBytes : sb + kOffVsEnd;
                        const size_t off = (size_t)(ik < kMain ? u : u - r) * kVsBytes;
                        bulk_load(dst, gvs + off, nvs, bar, pol);
                        bulk_load(dst + nvs, gvz + off, nvs, bar, pol);
                    }
                    do_k = extra || st == 0;
                    st++;
                    advance(sk, phk);
                } else if (iv < kMain) {
                    mbar_wait(bar_vempty + sv * 8, phv);
                    mbar_expect_tx(bar_vfull + sv * 8, kTile);
                    tensor_load_4d(sb + kOffV + sv * kTile, &map_v, 0, (unit0 + iv * kSplit) * (kTok / 8), bar_vfull + sv * 8, pol);
                    do_k = st < kUnits;
                    iv++;
                    advance(sv, phv);
                } else {
                    mbar_wait(bar_kempty + sk * 8, phk);
                    mbar_expect_tx(bar_kfull + sk * 8, kTile);
                    tensor_load_4d(sb + kOffK + sk * kTile, &map_w, r * 16, (unit0 - r + iv * kSplit) * (kTok / 4),
                                   bar_kfull + sk * 8, pol);
                    iv++;
                    advance(sk, phk);
                }
                if (j == kOps - 24) asm volatile("prefetch.tensormap [%0];" ::"l"(&map_w) : "memory");
            }
        }
        return;
    }

    const int g = lane >> 2, c = lane & 3;
    const int hsel = c >> 1;
    const int ohead = 2 * (c & 1) + hsel;
    const uint32_t* const xg = xch + (size_t)bh * kSplit * kXWords;

    if (warp == kCW + 1) {
        const uint32_t* xoin = pin(xg + kXo + ohead * kD + 16 * r + 2 * g);
        const uint32_t red_rd = pin(sb + kOffRed + lane * 16);
        uint32_t* const optr = pin(reinterpret_cast<uint32_t*>(out + (size_t)(bh * kRep + ohead) * kD + 16 * r + 2 * g));
        const uint32_t epoch = ld_relaxed(xch + kScrEpoch + blockIdx.x) + 1;
        const uint32_t tag = epoch & 1;
        __syncwarp();
        if (lane == 0) {
            asm volatile("st.shared.u32 [%0], %1;" ::"r"(sb + kOffTag), "r"(tag) : "memory");
            xch[kScrEpoch + blockIdx.x] = epoch;
        }
        asm volatile("bar.sync 0, %0;" ::"n"(kThreads) : "memory");
        mbar_wait(bar_sig, 0);
        uint4 ml;
        int it = 0;
        do {
            ml = ld_relaxed4(xg + g * kXWords + kXm + c * 4);
            if (++it > (1 << 22)) __trap();
        } while (__any_sync(0xffffffffu, stale(ml, tag)));
        float wm[kSplit], we[kSplit];
        {
            const float m = untagged(ml.x);
            float M = fmaxf(m, __shfl_xor_sync(0xffffffffu, m, 4));
            M = fmaxf(M, __shfl_xor_sync(0xffffffffu, M, 8));
            M = fmaxf(M, __shfl_xor_sync(0xffffffffu, M, 16));
            const float w = ex2(m - M);
            float L = w * untagged(ml.y);
            L += __shfl_xor_sync(0xffffffffu, L, 4);
            L += __shfl_xor_sync(0xffffffffu, L, 8);
            L += __shfl_xor_sync(0xffffffffu, L, 16);
            const float inv = 1.f / L;
            const float w0 = w * inv, w1 = ex2(untagged(ml.z) - M) * inv;
#pragma unroll
            for (int k = 0; k < kSplit; k++) {
                wm[k] = __shfl_sync(0xffffffffu, w0, k * 4 + ohead);
                we[k] = __shfl_sync(0xffffffffu, w1, k * 4 + ohead);
            }
        }
        mbar_wait(bar_sig + 8, 0);
        uint2 o[kSplit];
        uint32_t pending = (1u << kSplit) - 1;
        do {
#pragma unroll
            for (int k = 0; k < kSplit; k++)
                if (pending >> k & 1) o[k] = ld_relaxed2(xoin + k * kXWords);
            uint32_t bad = 0;
#pragma unroll
            for (int k = 0; k < kSplit; k++) bad |= (((o[k].x ^ tag) | (o[k].y ^ tag)) & 1) << k;
            pending = __reduce_or_sync(0xffffffffu, bad);
            if (++it > (1 << 22)) __trap();
        } while (pending);
        float y0 = 0.f, y1 = 0.f, u0 = 0.f, u1 = 0.f;
#pragma unroll
        for (int k = 0; k < kSplit; k++) {
            y0 += wm[k] * untagged(o[k].x);
            y1 += wm[k] * untagged(o[k].y);
        }
        if (lane == 0) tick(prog);
        sts128f(red_rd + kCW * 512, y0, y1, y0, y1);
        asm volatile("bar.sync 2, %0;" ::"n"(kCW * 32 + 32) : "memory");
#pragma unroll
        for (int k = 0; k < kCW; k++) {
            const float4 z = lds128f(red_rd + k * 512);
            y0 += we[2 * k] * z.x;
            y1 += we[2 * k] * z.y;
            u0 += we[2 * k + 1] * z.z;
            u1 += we[2 * k + 1] * z.w;
        }
        asm volatile("st.global.u32 [%0], %1;" ::"l"(optr), "r"(pack_bf16(y0 + u0, y1 + u1)) : "memory");
        return;
    }

    const int cw = warp - 1;
    const int par = g & 1;
    uint2 qf[4][2];
    {
        const __nv_bfloat16* qrow = q + (size_t)(bh * kRep + (g & 3)) * kD + 4 * c;
#pragma unroll
        for (int P = 0; P < 4; P++) {
            qf[P][0] = __ldg(reinterpret_cast<const uint2*>(qrow + 32 * P));
            qf[P][1] = __ldg(reinterpret_cast<const uint2*>(qrow + 32 * P + 16));
        }
    }
    const uint32_t k_lane = sb + kOffK + (16 * cw + g) * 512 + c * 16 + par * 64;
    const uint32_t ks_lane = sb + kOffKs + (cw >> 1) * (kD * 2) + c * 8 + par * 32;
    const uint32_t v_lane = sb + kOffV + cw * 1024 + (2 * c) * 128 + ((g ^ (2 * c)) * 16);
    const uint32_t vs_lane = sb + kOffVs + (2 * c) * 2;
    const uint32_t sc_rd = sb + kOffSc + ((g & 3) * 4 + c) * 16;
    const uint32_t sc_wr = sc_rd + cw * 256;
    uint32_t* const xme = xch + (size_t)blockIdx.x * kXWords;
    const bool reporter = threadIdx.x == 32;
    const int gather_at = kStepGather + (blockIdx.x & 31);

    float acc[2][4] = {};
    float m_run = -FLT_MAX, l_run = 0.f, m_pub = 0.f;
    float a0 = 1.f, a1 = 1.f;
    uint32_t pb[4][2] = {};
    uint32_t pn[4][2];
    uint4 pf[kEnd][2][2];
    int sk = 0, sv = 0, iv = 0;
    uint32_t phk = 0, phv = 0;

    asm volatile("bar.sync 0, %0;" ::"n"(kThreads) : "memory");
    const uint32_t tag = lds32(sb + kOffTag);
#pragma unroll 1
    for (int i = 0; i <= kUnits; i++) {
        if (i < kUnits) {
            mbar_wait(bar_kfull + sk * 8, phk);
            float sa[2][2][4] = {};
#pragma unroll
            for (int P = 0; P < 4; P++)
#pragma unroll
                for (int e = 0; e < 2; e++) {
                    const uint32_t ka = (k_lane ^ (e * 64)) + sk * kTile + P * 128;
                    const uint32_t ksa = (ks_lane ^ (e * 32)) + sk * (2 * kKsBytes) + P * 64;
                    const uint2 zr = lds64(ksa + kKsBytes);
                    const uint2 sc = lds64(ksa);
#pragma unroll
                    for (int u = 0; u < 2; u++) {
                        const int4 x = lds128(ka + u * 8 * 512);
                        mma_bf16(sa[u][e], qf[P][e].x, qf[P][e ^ 1].x, qf[P][e].y, qf[P][e ^ 1].y,
                                 dequant2(x.x, x.y, zr.x, sc.x), dequant2(x.z, x.w, zr.y, sc.y));
                    }
                }
            __syncwarp();
            if (lane == 0) mbar_arrive(bar_kempty + sk * 8);
            if (reporter) tick(prog);
            advance(sk, phk);
            if (g < 4) {
                const float2 t0 = logits2(sa[0][0][0] + sa[0][1][0], sa[0][0][3] + sa[0][1][3]);
                const float2 t1 = logits2(sa[1][0][0] + sa[1][1][0], sa[1][0][3] + sa[1][1][3]);
                sts128f(sc_wr + (i & 3) * 1024, t0.x, t0.y, t1.x, t1.y);
            }
            asm volatile("bar.sync 1, %0;" ::"n"(kCW * 32) : "memory");

            float4 t[4];
#pragma unroll
            for (int kk = 0; kk < 4; kk++) t[kk] = lds128f(sc_rd + (i & 3) * 1024 + kk * 256);
            float mx = m_run;
#pragma unroll
            for (int kk = 0; kk < 4; kk++) mx = fmaxf(mx, fmaxf(fmaxf(t[kk].x, t[kk].y), fmaxf(t[kk].z, t[kk].w)));
            mx = fmaxf(mx, __shfl_xor_sync(0xffffffffu, mx, 1));
            mx = fmaxf(mx, __shfl_xor_sync(0xffffffffu, mx, 2));
            const float alpha = ex2(m_run - mx);
            m_run = mx;
            a0 *= __shfl_sync(0xffffffffu, alpha, (c & 1) * 8);
            a1 *= __shfl_sync(0xffffffffu, alpha, (c & 1) * 8 + 4);
            float ls = 0.f;
#pragma unroll
            for (int kk = 0; kk < 4; kk++) {
                const float p0 = ex2(t[kk].x - mx), p1 = ex2(t[kk].y - mx), p2 = ex2(t[kk].z - mx), p3 = ex2(t[kk].w - mx);
                ls += (p0 + p1) + (p2 + p3);
                pn[kk][0] = split_p(p0, p1, g >= 4);
                pn[kk][1] = split_p(p2, p3, g >= 4);
            }
            l_run = l_run * alpha + ls;

            if (i >= kStepEndK && i < kStepEndK + kEnd) {
                if (i == kStepEndK + kEnd - 1) {
                    m_pub = mx;
                    if (cw < kEnd) {
                        uint32_t w[8];
#pragma unroll
                        for (int kk = 0; kk < 4; kk++) {
                            const float4 u = lds128f(sc_rd + ((kStepEndK + cw) & 3) * 1024 + kk * 256);
                            w[2 * kk] = split_p_tagged(ex2(u.x - mx), ex2(u.y - mx), g >= 4, tag);
                            w[2 * kk + 1] = split_p_tagged(ex2(u.z - mx), ex2(u.w - mx), g >= 4, tag);
                        }
                        st_relaxed4(xme + kXp + cw * 256 + lane * 4, w[0], w[1], w[2], w[3]);
                        st_relaxed4(xme + kXp + cw * 256 + lane * 4 + 128, w[4], w[5], w[6], w[7]);
                    }
                }
                continue;
            }
            if (i == gather_at) {
                int it = 0;
                uint32_t bad;
                do {
#pragma unroll
                    for (int e = 0; e < kEnd; e++)
#pragma unroll
                        for (int s = 0; s < 2; s++)
#pragma unroll
                            for (int h = 0; h < 2; h++)
                                pf[e][s][h] = ld_relaxed4(xg + (2 * cw + s) * kXWords + kXp + e * 256 + h * 128 + lane * 4);
                    bad = 0;
#pragma unroll
                    for (int e = 0; e < kEnd; e++)
#pragma unroll
                        for (int s = 0; s < 2; s++)
#pragma unroll
                            for (int h = 0; h < 2; h++) bad |= stale(pf[e][s][h], tag);
                    if (++it > (1 << 22)) __trap();
                } while (__any_sync(0xffffffffu, bad));
#pragma unroll
                for (int e = 0; e < kEnd; e++)
#pragma unroll
                    for (int s = 0; s < 2; s++)
#pragma unroll
                        for (int h = 0; h < 2; h++) {
                            uint4& p = pf[e][s][h];
                            p = make_uint4(p.x & ~1u, p.y & ~1u, p.z & ~1u, p.w & ~1u);
                        }
            }
            if (i == kUnits - 1 && cw == kCW - 1) {
                float l = l_run + __shfl_xor_sync(0xffffffffu, l_run, 1);
                l += __shfl_xor_sync(0xffffffffu, l, 2);
                if (c == 0 && g < 4) st_relaxed4(xme + kXm + g * 4, tagged(m_run, tag), tagged(l, tag), tagged(m_pub, tag), tag);
            }
        }
        if (i > 0) {
            const uint32_t va0 = v_lane + sv * kTile, va1 = va0 ^ (128 + 16);
            const uint32_t vsb = vs_lane + (iv & (kVsRing - 1)) * (2 * kVsBytes);
            uint32_t vs[4][2], vz[4][2];
#pragma unroll
            for (int kk = 0; kk < 4; kk++)
#pragma unroll
                for (int u = 0; u < 2; u++) {
                    vs[kk][u] = lds32(vsb + kk * 32 + u * 16);
                    vz[kk][u] = lds32(vsb + kVsBytes + kk * 32 + u * 16);
                }
            mbar_wait(bar_vfull + sv * 8, phv);
#pragma unroll
            for (int kk = 0; kk < 4; kk++) {
                const int4 x0 = lds128(va0 + kk * 8192);
                const int4 x1 = lds128(va1 + kk * 8192);
                const int4 x2 = lds128(va0 + kk * 8192 + 4096);
                const int4 x3 = lds128(va1 + kk * 8192 + 4096);
                mma_bf16(acc[0], dequant2(x0.x, x1.x, vz[kk][0], vs[kk][0]), dequant2(x0.y, x1.y, vz[kk][0], vs[kk][0]),
                         dequant2(x2.x, x3.x, vz[kk][1], vs[kk][1]), dequant2(x2.y, x3.y, vz[kk][1], vs[kk][1]),
                         pb[kk][0], pb[kk][1]);
                mma_bf16(acc[1], dequant2(x0.z, x1.z, vz[kk][0], vs[kk][0]), dequant2(x0.w, x1.w, vz[kk][0], vs[kk][0]),
                         dequant2(x2.z, x3.z, vz[kk][1], vs[kk][1]), dequant2(x2.w, x3.w, vz[kk][1], vs[kk][1]),
                         pb[kk][0], pb[kk][1]);
            }
            __syncwarp();
            if (lane == 0) mbar_arrive(bar_vempty + sv * 8);
            if (reporter) tick(prog);
            advance(sv, phv);
            iv++;
        }
#pragma unroll
        for (int m = 0; m < 2; m++) {
            acc[m][0] *= a0;
            acc[m][1] *= a1;
            acc[m][2] *= a0;
            acc[m][3] *= a1;
        }
        a0 = a1 = 1.f;
#pragma unroll
        for (int kk = 0; kk < 4; kk++) {
            pb[kk][0] = pn[kk][0];
            pb[kk][1] = pn[kk][1];
        }
    }

    auto fold = [&](const float (&a)[2][4], float (&y)[4]) {
#pragma unroll
        for (int m = 0; m < 2; m++)
#pragma unroll
            for (int e = 0; e < 2; e++)
                y[2 * m + e] = (hsel ? a[m][2 * e + 1] : a[m][2 * e]) +
                               __shfl_xor_sync(0xffffffffu, hsel ? a[m][2 * e] : a[m][2 * e + 1], 2);
    };
    float y[4];
    fold(acc, y);
    st_relaxed4(xme + kXo + ohead * kD + 32 * cw + 4 * g, tagged(y[0], tag), tagged(y[1], tag), tagged(y[2], tag),
                tagged(y[3], tag));

    const uint32_t w_lane =
        pin(sb + kOffK + cw * 8192 + ((c & 1) + 4 * hsel) * 64 + (((g >> 1) ^ (2 * hsel)) * 16) + (g & 1) * 8);
    const uint32_t red_wr = pin(sb + kOffRed + cw * 512 + lane * 16);
    float a[2][4] = {};
#pragma unroll 1
    for (int e = 0; e < kEnd; e++) {
        const uint32_t wa0 = w_lane + sk * kTile, wa1 = wa0 ^ (128 + 16);
        const uint32_t vsb = sb + kOffVsEnd + (e * kSplit * kTok + cw * 2 * kTok + 2 * c) * 2;
        uint32_t vs[8][2], vz[8][2];
#pragma unroll
        for (int k8 = 0; k8 < 8; k8++)
#pragma unroll
            for (int u = 0; u < 2; u++) {
                vs[k8][u] = lds32(vsb + k8 * 32 + u * 16);
                vz[k8][u] = lds32(vsb + kVsEndBytes + k8 * 32 + u * 16);
            }
        mbar_wait(bar_kfull + sk * 8, phk);
#pragma unroll
        for (int kk = 0; kk < 4; kk++)
#pragma unroll
            for (int s = 0; s < 2; s++) {
                const int k8 = s * 4 + kk;
                const uint2 x0 = lds64(wa0 + k8 * 1024);
                const uint2 x1 = lds64(wa1 + k8 * 1024);
                const uint2 x2 = lds64(wa0 + k8 * 1024 + 512);
                const uint2 x3 = lds64(wa1 + k8 * 1024 + 512);
                const uint4 p = pf[0][s][kk >> 1];
                mma_bf16(a[s], dequant2(x0.x, x1.x, vz[k8][0], vs[k8][0]), dequant2(x0.y, x1.y, vz[k8][0], vs[k8][0]),
                         dequant2(x2.x, x3.x, vz[k8][1], vs[k8][1]), dequant2(x2.y, x3.y, vz[k8][1], vs[k8][1]),
                         (kk & 1) ? p.z : p.x, (kk & 1) ? p.w : p.y);
            }
        if (e == kEnd - 1) break;
        if (reporter) tick(prog);
        advance(sk, phk);
#pragma unroll
        for (int n = 0; n + 1 < kEnd; n++)
#pragma unroll
            for (int s = 0; s < 2; s++)
#pragma unroll
                for (int h = 0; h < 2; h++) pf[n][s][h] = pf[n + 1][s][h];
    }
    fold(a, y);
    sts128f(red_wr, y[0], y[1], y[2], y[3]);
    asm volatile("bar.arrive 2, %0;" ::"n"(kCW * 32 + 32) : "memory");
}

typedef CUresult (*EncodeTiledFn)(CUtensorMap*, CUtensorMapDataType, cuuint32_t, void*, const cuuint64_t*,
                                  const cuuint64_t*, const cuuint32_t*, const cuuint32_t*, CUtensorMapInterleave,
                                  CUtensorMapSwizzle, CUtensorMapL2promotion, CUtensorMapFloatOOBfill);

}

extern "C" void kernel_launch(void* const* d_in, const int* in_sizes, int n_in, void* d_out, int out_size) {
    (void)in_sizes;
    (void)n_in;
    (void)out_size;
    static EncodeTiledFn encode = nullptr;
    static uint32_t* scratch = nullptr;
    if (!encode) {
        cudaGetSymbolAddress((void**)&scratch, g_scratch);
        cudaDriverEntryPointQueryResult qr;
        void* fn = nullptr;
        cudaGetDriverEntryPoint("cuTensorMapEncodeTiled", &fn, cudaEnableDefault, &qr);
        encode = (EncodeTiledFn)fn;
        cudaFuncSetAttribute(kivi_decode_kernel, cudaFuncAttributeMaxDynamicSharedMemorySize, kSmemBytes);
    }
    CUtensorMap map_v, map_w;
    const cuuint32_t estr[4] = {1, 1, 1, 1};
    {
        const cuuint64_t gdim[4] = {32, 8, 4, (cuuint64_t)kBH * kS / 8};
        const cuuint64_t gstr[3] = {512, 128, 4096};
        const cuuint32_t box[4] = {32, 8, 4, kTok / 8};
        encode(&map_v, CU_TENSOR_MAP_DATA_TYPE_INT32, 4, d_in[2], gdim, gstr, box, estr, CU_TENSOR_MAP_INTERLEAVE_NONE,
               CU_TENSOR_MAP_SWIZZLE_128B, CU_TENSOR_MAP_L2_PROMOTION_NONE, CU_TENSOR_MAP_FLOAT_OOB_FILL_NONE);
    }
    {
        const cuuint64_t gdim[4] = {kD, 2, 2, (cuuint64_t)kBH * kS / 4};
        const cuuint64_t gstr[3] = {1024, 512, 2048};
        const cuuint32_t box[4] = {16, 2, 2, kSplit * kTok / 4};
        encode(&map_w, CU_TENSOR_MAP_DATA_TYPE_INT32, 4, d_in[2], gdim, gstr, box, estr, CU_TENSOR_MAP_INTERLEAVE_NONE,
               CU_TENSOR_MAP_SWIZZLE_64B, CU_TENSOR_MAP_L2_PROMOTION_L2_256B, CU_TENSOR_MAP_FLOAT_OOB_FILL_NONE);
    }
    kivi_decode_kernel<<<kCtas, kThreads, kSmemBytes>>>(
        (const int*)d_in[1], (const __nv_bfloat16*)d_in[3], (const __nv_bfloat16*)d_in[4], (const __nv_bfloat16*)d_in[5],
        (const __nv_bfloat16*)d_in[6], (const __nv_bfloat16*)d_in[0], (__nv_bfloat16*)d_out, scratch, map_v, map_w);
}
```
